```python
import torch

def _softmax(x, axis=-1):
    return torch.softmax(x, dim=axis)

def _gelu(x):
    return torch.nn.functional.gelu(x, approximate='tanh')

def _silu(x):
    return torch.nn.functional.silu(x)

def _sigmoid(x):
    return torch.sigmoid(x)

def _layernorm(x, axis=-1, eps=1e-05):
    m = x.mean(dim=axis, keepdim=True)
    v = x.var(dim=axis, keepdim=True, unbiased=False)
    return (x - m) / torch.sqrt(v + eps)

def _scatter_add(tgt, idx, src, axis=0):
    return tgt.clone().index_add_(axis, idx, src)

def _segment_sum(src, seg, n):
    out = torch.zeros((n,) + src.shape[1:], dtype=src.dtype)
    return out.index_add_(0, seg, src)

def _pad(x, pw):
    flat = tuple((v for pair in reversed(pw) for v in pair))
    return torch.nn.functional.pad(x, flat)
kernel_name = 'adaLN_cond__gqa_block_cached__glu_gated_geglu__decode'

def setup_inputs():

    _w = lambda a: (lambda t: t.to(torch.bfloat16) if t.is_floating_point() else t)(torch.as_tensor(a))

    def _A_setup():
        B, Sq, D = (8, 1, 576)
        Hq, Hkv, Sk, Dh = (32, 16, 8192, 128)
        assert Hq % Hkv == 0, (Hq, Hkv)
        return {'x': _w((lambda *s: torch.randn(*s, dtype=torch.bfloat16) * 0.1)(B, Sq, D)), 'k_cache': _w((lambda *s: torch.randn(*s, dtype=torch.bfloat16) * 0.8)(B, Hkv, Sk, Dh)), 'v_cache': _w((lambda *s: torch.randn(*s, dtype=torch.bfloat16) * 3.2)(B, Hkv, Sk, Dh)), 'wq': _w((lambda *s: torch.randn(*s, dtype=torch.bfloat16) * 0.8)(D, Hq * Dh) * D ** (-0.5)), 'wo': _w((lambda *s: torch.randn(*s, dtype=torch.bfloat16) * 3.2)(Hq * Dh, D) * (Hq * Dh) ** (-0.5))}
    _A_in = _A_setup()

    def _B_setup():
        B, S, Dm, Df = (8, 1, 576, 4608)
        return {'x': _w((lambda *s: torch.randn(*s, dtype=torch.bfloat16) * 0.1)(B, S, Dm)), 'w_gate': _w((lambda *s: torch.randn(*s, dtype=torch.bfloat16) * 3.2)(Dm, Df) * Dm ** (-0.5)), 'w_up': _w((lambda *s: torch.randn(*s, dtype=torch.bfloat16) * 3.2)(Dm, Df) * Dm ** (-0.5)), 'w_down': _w((lambda *s: torch.randn(*s, dtype=torch.bfloat16) * 3.2)(Df, Dm) * Df ** (-0.5))}
    _B_in = _B_setup()
    return {'A_x': _A_in['x'], 'A_k_cache': _A_in['k_cache'], 'A_v_cache': _A_in['v_cache'], 'A_wq': _A_in['wq'], 'A_wo': _A_in['wo'], 'B_x': _B_in['x'], 'B_w_gate': _B_in['w_gate'], 'B_w_up': _B_in['w_up'], 'B_w_down': _B_in['w_down'], 'c': _w((lambda *s: torch.randn(*s, dtype=torch.bfloat16) * 0.4)(8, 576) * 8.0), 'w_mod': _w((lambda *s: torch.randn(*s, dtype=torch.bfloat16) * 0.4)(576, 6 * 576) * 576 ** (-0.5) * 8.0)}

def reference(A_x, A_k_cache, A_v_cache, A_wq, A_wo, B_x, B_w_gate, B_w_up, B_w_down, c, w_mod):

    def _A_ref(x, k_cache, v_cache, wq, wo):
        B, Sq, D = x.shape
        Hq, Dh = (32, 128)
        Hkv = k_cache.shape[1]
        rep = Hq // Hkv
        q = (lambda x, *d: x.permute(*d))((x @ wq).reshape(B, Sq, Hq, Dh), 0, 2, 1, 3)
        k = (lambda x, n, axis: torch.repeat_interleave(x, n, dim=axis))(k_cache, rep, axis=1)
        v = (lambda x, n, axis: torch.repeat_interleave(x, n, dim=axis))(v_cache, rep, axis=1)
        scores = torch.einsum('bhqd,bhkd->bhqk', q, k) * Dh ** (-0.5)
        p = _softmax(scores, axis=-1)
        o = torch.einsum('bhqk,bhkd->bhqd', p, v)
        return (lambda x, *d: x.permute(*d))(o, 0, 2, 1, 3).reshape(B, Sq, Hq * Dh) @ wo

    def _B_ref(x, w_gate, w_up, w_down):
        g = torch.einsum('bsd,df->bsf', x, w_gate)
        u = torch.einsum('bsd,df->bsf', x, w_up)
        h = _gelu(g) * u
        return torch.einsum('bsf,fd->bsd', h, w_down)
    x = A_x
    mod = (_silu(c) @ w_mod).reshape(c.shape[0], 6, 1, -1)
    sa, ca, ga, sb, cb, gb = (mod[:, 0].clone(), mod[:, 1].clone(), mod[:, 2].clone(), mod[:, 3].clone(), mod[:, 4].clone(), mod[:, 5].clone())
    h = _layernorm(x, axis=-1) * (1 + ca) + sa
    x = x + ga * _A_ref(h, A_k_cache, A_v_cache, A_wq, A_wo)
    h = _layernorm(x, axis=-1) * (1 + cb) + sb
    x = x + gb * _B_ref(h, B_w_gate, B_w_up, B_w_down)
    return x
```

```cpp
#include <cuda_runtime.h>
#include <cuda_bf16.h>
#include <cuda.h>
#include <stdint.h>
#include <stddef.h>

namespace {

typedef unsigned long long u64;

constexpr int NB = 8;
constexpr int DM = 576;
constexpr int SK = 8192;
constexpr int DF = 4608;
constexpr int NCTA = 128;
constexpr int NTHREADS = 288;

constexpr int NSLOT = 12;
constexpr int SLOT = 16384;
constexpr int RING = NSLOT * SLOT;
constexpr int P_REG = DM * 64;
constexpr int P_A = 3 * SLOT;
constexpr int P_B = P_A + P_REG;
constexpr int T_WO = 0;
constexpr int T_WG = T_WO + 256 * 144;
constexpr int T_WU = T_WG + DM * 80;
constexpr int T_WD = T_WU + DM * 80;
constexpr int T_END = T_WD + 288 * 144;
static_assert(T_END <= RING, "tail overlay");
static_assert(P_B + P_REG <= 8 * SLOT, "prologue overlay");
constexpr int ACT_PITCH = 1168;
constexpr int OFF_ACT = RING;
constexpr int OFF_RED = OFF_ACT + NB * ACT_PITCH;
constexpr int RED_BYTES = 12288 + 256;
constexpr int ACTB_O_PITCH = 528;
constexpr int ACTB_H_PITCH = 592;
constexpr int OFF_ACTB = OFF_RED + RED_BYTES;
constexpr int OFF_STAT = OFF_ACTB + NB * ACTB_H_PITCH;
constexpr int OFF_BAR = OFF_STAT + 128;
constexpr int BAR_FULL = 0, BAR_EMPTY = NSLOT, BAR_P = 2 * NSLOT, BAR_T = BAR_P + 6;
constexpr int NT_PIECES = 11;
constexpr int BAR_CRIT = BAR_T + NT_PIECES;
constexpr int NBARS = BAR_CRIT + 1;
constexpr int OFF_Q = OFF_BAR + NBARS * 8;
constexpr int OFF_STAMP = OFF_Q + 16 * 8;
constexpr int SMEM_USED = OFF_STAMP + 64 * 8;
constexpr int SMEM_BYTES = SMEM_USED + 1024;
static_assert(SMEM_BYTES <= 232448, "smem");

constexpr int NTILES = 256;
constexpr int TILE0 = 8;
constexpr int TILE_END = TILE0 + NTILES;

#define PACE_D0 4
#define PACE_GAIN 6
#define PACE_DMIN 3
#define PACE_DMAX 8
#define PACE_DSTART 3
#define WIN_P 45056
#define START_TILES 2
#define WIN_T 49152
#define NEARLY 0

#define CRIT_FIRST 0
#define PF_TILES 0
constexpr int PH2 = NEARLY > 0 ? 248 : 1000;
#define DRY_P 0
#define DRY_T 0
#define PREFETCH_TM 1
constexpr int SPIN_LIMIT = 1 << 22;

struct Scratch {
    u64 h0[NB][288];
    u64 mod[NB][1152];
    u64 q[16][NB][128];
    u64 o[16][NB][128];
    u64 p1[8][16][16][36];
    u64 x1[NB][96][2];
    u64 hh[16][144][NB];
    u64 p2[8][16][16][36];
    unsigned int epoch, pad0[31];
    unsigned int prog, pad1[31];
};
__device__ __align__(1024) Scratch g_scr;
constexpr int P2_MINUS_P1 = (int)((offsetof(Scratch, p2) - offsetof(Scratch, p1)) / 8);

#define PIN32(x) asm volatile("" : "+r"(x))
#define PIN64(x) asm volatile("" : "+l"(x))

__device__ __forceinline__ uint32_t smem_u32(const void* p) { return (uint32_t)__cvta_generic_to_shared(p); }
__device__ __forceinline__ void sts32(uint32_t a, uint32_t v) { asm volatile("st.shared.b32 [%0], %1;" ::"r"(a), "r"(v) : "memory"); }
__device__ __forceinline__ void sts64f(uint32_t a, float x, float y) { asm volatile("st.shared.v2.f32 [%0], {%1, %2};" ::"r"(a), "f"(x), "f"(y) : "memory"); }
__device__ __forceinline__ void sts128f(uint32_t a, float x, float y, float z, float w) {
    asm volatile("st.shared.v4.f32 [%0], {%1, %2, %3, %4};" ::"r"(a), "f"(x), "f"(y), "f"(z), "f"(w) : "memory");
}
__device__ __forceinline__ uint32_t lds32(uint32_t a) { uint32_t v; asm volatile("ld.shared.b32 %0, [%1];" : "=r"(v) : "r"(a)); return v; }
__device__ __forceinline__ float ldsf(uint32_t a) { float v; asm volatile("ld.shared.f32 %0, [%1];" : "=f"(v) : "r"(a)); return v; }
__device__ __forceinline__ float4 lds128f(uint32_t a) {
    float4 v;
    asm volatile("ld.shared.v4.f32 {%0, %1, %2, %3}, [%4];" : "=f"(v.x), "=f"(v.y), "=f"(v.z), "=f"(v.w) : "r"(a));
    return v;
}

#define STAMP(i) do {} while (0)

__device__ __forceinline__ void mbar_init(uint32_t bar, uint32_t cnt) {
    asm volatile("mbarrier.init.shared::cta.b64 [%0], %1;" ::"r"(bar), "r"(cnt) : "memory");
}
__device__ __forceinline__ void mbar_expect_tx(uint32_t bar, uint32_t bytes) {
    asm volatile("mbarrier.arrive.expect_tx.shared::cta.b64 _, [%0], %1;" ::"r"(bar), "r"(bytes) : "memory");
}
__device__ __forceinline__ void mbar_arrive(uint32_t bar) {
    asm volatile("mbarrier.arrive.shared::cta.b64 _, [%0];" ::"r"(bar) : "memory");
}
__device__ __forceinline__ void mbar_arrive_n(uint32_t bar, uint32_t n) {
    asm volatile("mbarrier.arrive.shared::cta.b64 _, [%0], %1;" ::"r"(bar), "r"(n) : "memory");
}
__device__ __forceinline__ void mbar_wait(uint32_t bar, uint32_t parity) {
    asm volatile(
        "{\n.reg .pred p;\n.reg .u32 n;\nmov.u32 n, 0;\n"
        "W: mbarrier.try_wait.parity.shared::cta.b64 p, [%0], %1;\n"
        "@p bra D;\nadd.u32 n, n, 1;\nsetp.lt.u32 p, n, %2;\n@p bra W;\ntrap;\nD:\n}"
        ::"r"(bar), "r"(parity), "n"(SPIN_LIMIT) : "memory");
}
__device__ __forceinline__ void cbar() { asm volatile("bar.sync 1, 256;" ::: "memory"); }

__device__ __forceinline__ void tma2d(uint32_t dst, const CUtensorMap* tm, int c0, int c1, uint32_t bar) {
    asm volatile("cp.async.bulk.tensor.2d.shared::cluster.global.mbarrier::complete_tx::bytes [%0], [%1, {%3, %4}], [%2];"
                 ::"r"(dst), "l"(tm), "r"(bar), "r"(c0), "r"(c1) : "memory");
}
__device__ __forceinline__ void tma3d_hint(uint32_t dst, const CUtensorMap* tm, int c0, int c1, int c2, uint32_t bar, uint64_t pol) {
    asm volatile("cp.async.bulk.tensor.3d.shared::cluster.global.mbarrier::complete_tx::bytes.L2::cache_hint [%0], [%1, {%3, %4, %5}], [%2], %6;"
                 ::"r"(dst), "l"(tm), "r"(bar), "r"(c0), "r"(c1), "r"(c2), "l"(pol) : "memory");
}
__device__ __forceinline__ void ldsm4(uint32_t (&r)[4], uint32_t a) {
    asm volatile("ldmatrix.sync.aligned.m8n8.x4.shared.b16 {%0,%1,%2,%3}, [%4];"
                 : "=r"(r[0]), "=r"(r[1]), "=r"(r[2]), "=r"(r[3]) : "r"(a));
}
__device__ __forceinline__ void ldsm4t(uint32_t (&r)[4], uint32_t a) {
    asm volatile("ldmatrix.sync.aligned.m8n8.x4.trans.shared.b16 {%0,%1,%2,%3}, [%4];"
                 : "=r"(r[0]), "=r"(r[1]), "=r"(r[2]), "=r"(r[3]) : "r"(a));
}
__device__ __forceinline__ void ldsm2(uint32_t& r0, uint32_t& r1, uint32_t a) {
    asm volatile("ldmatrix.sync.aligned.m8n8.x2.shared.b16 {%0,%1}, [%2];" : "=r"(r0), "=r"(r1) : "r"(a));
}
__device__ __forceinline__ void mma16816(float (&c)[4], const uint32_t (&a)[4], uint32_t b0, uint32_t b1) {
    asm volatile("mma.sync.aligned.m16n8k16.row.col.f32.bf16.bf16.f32 {%0,%1,%2,%3}, {%4,%5,%6,%7}, {%8,%9}, {%0,%1,%2,%3};"
                 : "+f"(c[0]), "+f"(c[1]), "+f"(c[2]), "+f"(c[3])
                 : "r"(a[0]), "r"(a[1]), "r"(a[2]), "r"(a[3]), "r"(b0), "r"(b1));
}
__device__ __forceinline__ uint32_t movmat(uint32_t a) {
    uint32_t d;
    asm volatile("movmatrix.sync.aligned.m8n8.trans.b16 %0, %1;" : "=r"(d) : "r"(a));
    return d;
}
__device__ __forceinline__ float ex2(float x) {
    float y;
    asm("ex2.approx.ftz.f32 %0, %1;" : "=f"(y) : "f"(x));
    return y;
}
__device__ __forceinline__ uint32_t pack_bf16(float lo, float hi) {
    __nv_bfloat162 v = __floats2bfloat162_rn(lo, hi);
    return *reinterpret_cast<uint32_t*>(&v);
}
__device__ __forceinline__ float bf_lo(uint32_t v) { return __uint_as_float(v << 16); }
__device__ __forceinline__ float bf_hi(uint32_t v) { return __uint_as_float(v & 0xffff0000u); }
__device__ __forceinline__ float rbf(float x) { return __bfloat162float(__float2bfloat16_rn(x)); }

__device__ __forceinline__ void ll_st(u64* p, uint32_t data, uint32_t tag) {
    asm volatile("{\n.reg .b64 v;\nmov.b64 v, {%1, %2};\nst.relaxed.gpu.global.b64 [%0], v;\n}" ::"l"(p), "r"(data), "r"(tag) : "memory");
}
__device__ __forceinline__ void ll_ld(const u64* p, uint32_t& data, uint32_t& tg) {
    asm volatile("{\n.reg .b64 v;\nld.relaxed.gpu.global.b64 v, [%2];\nmov.b64 {%0, %1}, v;\n}" : "=r"(data), "=r"(tg) : "l"(p) : "memory");
}
__device__ __forceinline__ void ll_ld2(const u64* p, uint32_t& d0, uint32_t& t0, uint32_t& d1, uint32_t& t1) {
    asm volatile("{\n.reg .b64 a, b;\nld.relaxed.gpu.global.v2.b64 {a, b}, [%4];\nmov.b64 {%0, %1}, a;\nmov.b64 {%2, %3}, b;\n}"
                 : "=r"(d0), "=r"(t0), "=r"(d1), "=r"(t1) : "l"(p) : "memory");
}
__device__ __forceinline__ void ll_st128(u64* p, uint32_t w0, uint32_t w1, uint32_t w2, uint32_t tag) {
    asm volatile("{\n.reg .b128 r;\n.reg .b64 lo, hi;\nmov.b64 lo, {%1, %2};\nmov.b64 hi, {%3, %4};\nmov.b128 r, {lo, hi};\n"
                 "st.relaxed.gpu.global.b128 [%0], r;\n}" ::"l"(p), "r"(w0), "r"(w1), "r"(w2), "r"(tag) : "memory");
}
__device__ __forceinline__ void ll_ld128(const u64* p, uint32_t& w0, uint32_t& w1, uint32_t& w2, uint32_t& tg) {
    asm volatile("{\n.reg .b128 r;\n.reg .b64 lo, hi;\nld.relaxed.gpu.global.b128 r, [%4];\nmov.b128 {lo, hi}, r;\n"
                 "mov.b64 {%0, %1}, lo;\nmov.b64 {%2, %3}, hi;\n}" : "=r"(w0), "=r"(w1), "=r"(w2), "=r"(tg) : "l"(p) : "memory");
}
__device__ __forceinline__ bool poll_done(uint32_t bad, int& it) {
    if (!__any_sync(0xffffffffu, bad != 0)) return true;
    if (++it > SPIN_LIMIT) __trap();
    return false;
}
template <int N, int STRIDE>
__device__ __forceinline__ void ll_poll(const u64* p, uint32_t tag, uint32_t (&out)[N]) {
    int it = 0;
    uint32_t bad;
    do {
        bad = 0;
#pragma unroll
        for (int i = 0; i < N; i++) { uint32_t tg; ll_ld(p + i * STRIDE, out[i], tg); bad |= tg ^ tag; }
    } while (!poll_done(bad, it));
}
__device__ __forceinline__ void reduce16(const u64* p, uint32_t buf, int warp, int lane, uint32_t tag, bool live, float& s0, float& s1) {
    uint32_t a0 = 0, a1 = 0, b0 = 0, b1 = 0;
    if (live) {
        int it = 0;
        uint32_t bad;
        do {
            uint32_t t0, t1, t2, t3;
            ll_ld2(p, a0, t0, a1, t1);
            ll_ld2(p + 36, b0, t2, b1, t3);
            bad = ((t0 ^ tag) | (t1 ^ tag)) | ((t2 ^ tag) | (t3 ^ tag));
        } while (!poll_done(bad, it));
    }
    if (lane < 18) sts64f(buf + (warp * 18 + lane) * 8, __uint_as_float(a0) + __uint_as_float(b0), __uint_as_float(a1) + __uint_as_float(b1));
    if (warp != 7) {
        asm volatile("bar.arrive 3, 256;" ::: "memory");
    } else {
        asm volatile("bar.sync 3, 256;" ::: "memory");
        float x[8], y[8];
        const uint32_t q = buf + (lane < 18 ? lane : 0) * 8;
#pragma unroll
        for (int w = 0; w < 8; w++) asm volatile("ld.shared.v2.f32 {%0, %1}, [%2];" : "=f"(x[w]), "=f"(y[w]) : "r"(q + w * 144));
        s0 = ((x[0] + x[1]) + (x[2] + x[3])) + ((x[4] + x[5]) + (x[6] + x[7]));
        s1 = ((y[0] + y[1]) + (y[2] + y[3])) + ((y[4] + y[5]) + (y[6] + y[7]));
    }
}

__device__ __forceinline__ void ln_stats(const uint32_t (&v)[9], float& mean, float& rstd) {
    const float k = __shfl_sync(0xffffffffu, bf_lo(v[0]), 0);
    float s = 0.f, q = 0.f;
#pragma unroll
    for (int i = 0; i < 9; i++) {
        const float a = bf_lo(v[i]) - k, b = bf_hi(v[i]) - k;
        s += a + b;
        q = fmaf(a, a, fmaf(b, b, q));
    }
#pragma unroll
    for (int o = 16; o > 0; o >>= 1) { s += __shfl_xor_sync(0xffffffffu, s, o); q += __shfl_xor_sync(0xffffffffu, q, o); }
    const float md = s * (1.0f / DM);
    mean = k + md;
    rstd = rsqrtf(fmaxf(q * (1.0f / DM) - md * md, 0.f) + 1e-5f);
}
__device__ __forceinline__ float silu_f(float a) { return __fdividef(a, 1.f + __expf(-a)); }
__device__ __forceinline__ float gelu_f(float g) {
    const float z2 = 1.5957691216057308f * fmaf(0.044715f * g * g, g, g);
    return __fdividef(g, 1.f + __expf(-z2));
}

template <int KSTEPS>
__device__ __forceinline__ void gemv72_load(uint32_t (&a)[KSTEPS][4], uint32_t aaddr) {
#pragma unroll
    for (int i = 0; i < KSTEPS; i++) ldsm4t(a[i], aaddr + i * 16 * 144);
}
template <int KSTEPS>
__device__ __forceinline__ void gemv72_run(const uint32_t (&a)[KSTEPS][4], uint32_t baddr, u64* p0, u64* p1, bool hi_ok, uint32_t tag, bool live, uint32_t sb = 0, int st0 = -1) {
    float c[4][4];
#pragma unroll
    for (int j = 0; j < 4; j++) c[j][0] = c[j][1] = c[j][2] = c[j][3] = 0.f;
#pragma unroll
    for (int i = 0; i < KSTEPS; i += 2) {
        uint32_t b[4];
        ldsm4(b, baddr + i * 32);
        mma16816(c[i & 3], a[i], b[0], b[1]);
        mma16816(c[(i + 1) & 3], a[i + 1], b[2], b[3]);
    }
    const float r0 = (c[0][0] + c[1][0]) + (c[2][0] + c[3][0]), r1 = (c[0][1] + c[1][1]) + (c[2][1] + c[3][1]);
    const float r2 = (c[0][2] + c[1][2]) + (c[2][2] + c[3][2]), r3 = (c[0][3] + c[1][3]) + (c[2][3] + c[3][3]);
    if (live) { ll_st(p0, __float_as_uint(r0), tag); ll_st(p0 + 2 * 576, __float_as_uint(r1), tag); }
    if (live && hi_ok) { ll_st(p1, __float_as_uint(r2), tag); ll_st(p1 + 2 * 576, __float_as_uint(r3), tag); }
}

struct Params {
    const __nv_bfloat16* x;
    const __nv_bfloat16* c;
    const __nv_bfloat16* wmod;
    const __nv_bfloat16* k;
    const __nv_bfloat16* v;
    __nv_bfloat16* out;
    Scratch* scr;
};

__global__ void __launch_bounds__(NTHREADS, 1)
adaln_gqa_geglu_decode_kernel(const Params prm,
                              const __grid_constant__ CUtensorMap tmK, const __grid_constant__ CUtensorMap tmV,
                              const __grid_constant__ CUtensorMap tmMod, const __grid_constant__ CUtensorMap tmWq,
                              const __grid_constant__ CUtensorMap tmWo, const __grid_constant__ CUtensorMap tmWg,
                              const __grid_constant__ CUtensorMap tmWu, const __grid_constant__ CUtensorMap tmWd) {
    extern __shared__ unsigned char smem_raw[];
    uint32_t sb = (smem_u32(smem_raw) + 1023u) & ~1023u;
    int tid = threadIdx.x, cta = blockIdx.x;
    Scratch* scr = prm.scr;
    PIN32(sb); PIN32(tid); PIN32(cta); PIN64(scr);
    const uint32_t bars = sb + OFF_BAR;
    const int warp = tid >> 5, lane = tid & 31;
    const int grp = cta >> 3, mem = cta & 7;
    const bool has_mod = cta < 108;

    if (warp == 8) {
        if (lane >= 16 && lane < 16 + PF_TILES) {
            const int i = lane - 16;
            const __nv_bfloat16* src = ((i & 1) ? prm.v : prm.k) + ((size_t)(mem * 16 + grp) * SK + (i >> 1) * 64) * 128;
            uint64_t pol;
            asm volatile("createpolicy.fractional.L2::evict_first.b64 %0, 1.0;" : "=l"(pol));
            asm volatile("cp.async.bulk.prefetch.L2.global.L2::cache_hint [%0], %1, %2;" ::"l"(src), "r"(SLOT), "l"(pol) : "memory");
        }
        if (PREFETCH_TM && lane < 8) {
            const CUtensorMap* tm = lane == 0 ? &tmMod : lane == 1 ? &tmWq : lane == 2 ? &tmK : lane == 3 ? &tmV
                                  : lane == 4 ? &tmWo : lane == 5 ? &tmWg : lane == 6 ? &tmWu : &tmWd;
            asm volatile("prefetch.tensormap [%0];" ::"l"(tm) : "memory");
        }
        if (lane == 0) {
            STAMP(0);
        }
        if (lane == 0) {
#pragma unroll
            for (int s = 0; s < NBARS; s++) mbar_init(bars + 8 * s, (s >= BAR_EMPTY && s < BAR_P) ? 4 : 1);
#pragma unroll
            for (int s = 0; s < 8; s++) {
                mbar_arrive(bars + 8 * (BAR_FULL + s));
                if (s < 3 || (s >= 6 && !has_mod)) mbar_arrive_n(bars + 8 * (BAR_EMPTY + s), 4);
            }
            asm volatile("fence.mbarrier_init.release.cluster;" ::: "memory");
        }
        __syncwarp();
        if (lane == 0) STAMP(41);
        asm volatile("bar.arrive 2, 288;" ::: "memory");
        if (lane == 0) {
            uint64_t pol;
            asm volatile("createpolicy.fractional.L2::evict_first.b64 %0, 1.0;" : "=l"(pol));
            if (CRIT_FIRST && cta < 36) mbar_wait(bars + 8 * BAR_CRIT, 0);
            const uint32_t fifo = sb + OFF_Q;
            const int row0 = (mem * 16 + grp) * SK;
            const int boxcol = (36 * cta) & ~7;
            const int np = has_mod ? 6 : 3, np_first = cta < 36 ? 6 : 3;
            int head = 0, tail = 0, inflight = 0;
            int pi = cta < 36 ? 3 : 0, tp = TILE0, ti = 0, freed = 0, slot = TILE0, use = 0, win = PACE_DSTART, own_at = 0;
            unsigned gpend = 0;
            bool tdue = false;
#pragma unroll 1
            while (true) {
                uint32_t bar, par = 0;
                int bytes, window, kind;
                if (pi < np && (pi < np_first || tp >= TILE0 + START_TILES)) {
                    kind = 0; bar = bars + 8 * (BAR_P + pi); bytes = 12288;
                    window = pi < np_first ? (1 << 30) : WIN_P;
                } else if (tp < TILE_END && !tdue) {
                    kind = 1;
                    if (use > 0) mbar_wait(bars + 8 * (BAR_EMPTY + slot), (use - 1) & 1);
                    if (PACE_GAIN > 0 && (tp & 1) == 0) {
                        if (tp >= TILE0 + 12) {
                            const int sc = (own_at * NCTA - (int)gpend) * PACE_GAIN;
                            const int adj = sc >= 0 ? (sc + 2 * NCTA) / (4 * NCTA) : -((-sc + 2 * NCTA) / (4 * NCTA));
                            win = min(max(PACE_D0 - adj, PACE_DMIN), tp >= PH2 - 4 ? min(PACE_DMAX, 4) : PACE_DMAX);
                        }
                        asm volatile("red.relaxed.gpu.global.add.u32 [%0], 1;" ::"l"(&scr->prog) : "memory");
                        own_at = ((tp - TILE0) >> 1) + 1;
                        asm volatile("ld.relaxed.gpu.global.u32 %0, [%1];" : "=r"(gpend) : "l"(&scr->prog) : "memory");
                    } else if (PACE_GAIN == 0 && tp >= TILE0 + 12) win = PACE_D0;
                    bar = bars + 8 * (BAR_FULL + slot); par = use & 1; bytes = SLOT; window = tp < TILE0 + START_TILES ? (1 << 30) : win * SLOT;
                } else if (ti < NT_PIECES) {
                    kind = 2;
                    bytes = ti < 2 ? 18432 : ti < 8 ? 15360 : 13824;
                    const int end = ti < 2 ? 18432 * (ti + 1) : ti < 8 ? T_WG + 15360 * (ti - 1) : T_WD + 13824 * (ti - 7);
                    while (freed * SLOT < end) { mbar_wait(bars + 8 * (BAR_EMPTY + freed), (NEARLY > 0 && freed < 8) ? 0 : 1); freed++; }
                    bar = bars + 8 * (BAR_T + ti);
                    window = tp < TILE_END ? win * SLOT : WIN_T;
                } else break;
                while (head != tail && inflight + bytes > window) {
                    const uint32_t e = lds32(fifo + 8 * (head & 15));
                    mbar_wait(e & ~1u, e & 1u);
                    inflight -= (int)lds32(fifo + 8 * (head & 15) + 4);
                    head++;
                }
                sts32(fifo + 8 * (tail & 15), bar | par); sts32(fifo + 8 * (tail & 15) + 4, bytes);
                tail++; inflight += bytes;
                mbar_expect_tx(bar, bytes);
                if (kind == 0) {
                    const int r = pi >= 3 ? 1 : 0, pp = pi - 3 * r;
                    const bool is_q = (cta < 36) == (r == 1);
                    tma2d(sb + (r ? P_B : P_A) + pp * 12288, is_q ? &tmWq : &tmMod, is_q ? 32 * cta : 1152 + 32 * (cta - 36), 192 * pp, bar);
                    pi++;
                } else if (kind == 1) {
                    tma3d_hint(sb + slot * SLOT, (tp & 1) ? &tmV : &tmK, 0, row0 + ((tp - TILE0) >> 1) * 64, 0, bar, pol);
                    tdue = tp >= PH2 && (tp & 1) && ti < NEARLY;
                    if (++slot == NSLOT) { slot = tp < PH2 + 3 ? 0 : 8; use++; }
                    tp++;
                } else {
                    const CUtensorMap* tm = ti < 2 ? &tmWo : ti < 5 ? &tmWg : ti < 8 ? &tmWu : &tmWd;
                    const int off = ti < 2 ? 18432 * ti : ti < 8 ? T_WG + 15360 * (ti - 2) : T_WD + 13824 * (ti - 8);
                    const int c0 = (ti >= 2 && ti < 8) ? boxcol : 72 * mem;
                    const int c1 = ti < 2 ? 256 * grp + 128 * ti : ti < 5 ? 192 * (ti - 2) : ti < 8 ? 192 * (ti - 5) : 288 * grp + 96 * (ti - 8);
                    tma2d(sb + off, tm, c0, c1, bar);
                    ti++; tdue = false;
                }
            }
            STAMP(2);
        }
        return;
    }

    const int g = lane >> 2, t = lane & 3;
    const uint32_t act = sb + OFF_ACT, red = sb + OFF_RED, stat = sb + OFF_STAT;
    const uint32_t act_row = act + warp * ACT_PITCH;

    uint32_t xpair = 0;
    uint32_t cv[9];
    {
        unsigned ep = 0;
        if (tid == 0) asm volatile("ld.relaxed.gpu.global.u32 %0, [%1];" : "=r"(ep) : "l"(&scr->epoch) : "memory");
        if (cta < 36) {
            const int sub = tid & 3, row = tid >> 2;
            const char* src = reinterpret_cast<const char*>(prm.wmod) + row * (6 * DM * 2) + ((sub >> 1) * DM + 16 * cta) * 2 + (sub & 1) * 16;
            const uint32_t dst = sb + P_A + row * 64 + ((sub ^ ((row >> 1) & 3)) << 4);
#pragma unroll
            for (int j = 0; j < 9; j++)
                asm volatile("cp.async.cg.shared.global [%0], [%1], 16;" ::"r"(dst + j * 64 * 64), "l"(src + (size_t)j * 64 * (6 * DM * 2)) : "memory");
        }
        if (has_mod) {
            const uint32_t* crow = reinterpret_cast<const uint32_t*>(prm.c + warp * DM) + lane;
#pragma unroll
            for (int k = 0; k < 9; k++) cv[k] = __ldg(crow + 32 * k);
        }
        if (tid < 128) {
            ll_st(&scr->q[grp][tid >> 4][16 * mem + (tid & 15)], 0, 0);
            if (cta < 36) { if (tid < 64) ll_st(&scr->h0[tid >> 3][8 * cta + (tid & 7)], 0, 0); }
            else if (has_mod) ll_st(&scr->mod[tid >> 4][16 * (cta - 36) + (tid & 15)], 0, 0);
        }
        if (cta < 36) {
            const uint32_t* xrow = reinterpret_cast<const uint32_t*>(prm.x + warp * DM) + lane;
            uint32_t xv[9];
#pragma unroll
            for (int k = 0; k < 9; k++) xv[k] = __ldg(xrow + 32 * k);
            if (tid < 64) xpair = __ldg(reinterpret_cast<const uint32_t*>(prm.x + (tid >> 3) * DM + 16 * cta) + (tid & 7));
            float mean, rstd;
            ln_stats(xv, mean, rstd);
            if (lane == 0) sts64f(stat + 8 * warp, mean, rstd);
        }
        if (tid == 32) STAMP(44);
        if (tid == 0) sts32(stat + 64, ep + 1);
        if (tid == 0) STAMP(45);
    }
    asm volatile("bar.sync 2, 288;" ::: "memory");
    const uint32_t tag = lds32(stat + 64);
    if (tid == 0) STAMP(14);

    const int pass0 = (DRY_P && cta >= 36) ? -1 : 0;
#pragma unroll 1
    for (int pass = pass0; pass < 2; pass++) {
        const bool dry = pass < 0;
        const int st = dry ? 0 : pass;
        const bool is_q = (cta < 36) == (st == 1);
        if (!is_q && !has_mod) break;
        uint32_t av[9];
        if (!is_q && !dry) {
#pragma unroll
            for (int k = 0; k < 9; k++) av[k] = pack_bf16(silu_f(bf_lo(cv[k])), silu_f(bf_hi(cv[k])));
        }
        if (dry) {
#pragma unroll
            for (int k = 0; k < 9; k++) av[k] = 0;
        } else if (!is_q && cta < 36) {
            asm volatile("cp.async.wait_all;" ::: "memory");
        } else {
#pragma unroll 1
            for (int p = 0; p < 3; p++) mbar_wait(bars + 8 * (BAR_P + 3 * st + p), 0);
        }
        if (tid == 0) STAMP(15 + st);
        if (is_q && !dry) ll_poll<9, 32>(&scr->h0[warp][lane], tag, av);
        if (tid == 0 && is_q) STAMP(50);
        if (tid == 224 && is_q) STAMP(51);
        if (pass > pass0) cbar();
#pragma unroll
        for (int k = 0; k < 9; k++) sts32(act_row + 4 * (lane + 32 * k), av[k]);
        cbar();
        if (CRIT_FIRST && tid == 0 && !is_q && cta < 36) mbar_arrive(bars + 8 * BAR_CRIT);
        if (tid == 0) STAMP(is_q ? 4 : 3);
        {
            const int mt = warp & 1, kg = warp >> 1;
            const int rl = (lane & 7) + ((lane >> 4) << 3);
            const uint32_t aaddr = sb + (st ? P_B : P_A) + (144 * kg + rl) * 64 + (((2 * mt + ((lane >> 3) & 1)) ^ ((rl >> 1) & 3)) << 4);
            const uint32_t baddr = act + (lane & 7) * ACT_PITCH + ((lane >> 3) & 1) * 16 + 288 * kg;
            float c0[4] = {0.f, 0.f, 0.f, 0.f}, c1[4] = {0.f, 0.f, 0.f, 0.f};
#pragma unroll
            for (int i = 0; i < 9; i++) {
                uint32_t a[4], b0, b1;
                ldsm4t(a, aaddr + i * 16 * 64);
                ldsm2(b0, b1, baddr + i * 32);
                if (i & 1) mma16816(c1, a, b0, b1); else mma16816(c0, a, b0, b1);
            }
            const uint32_t dst = red + warp * 512 + g * 32 + t * 8;
            sts64f(dst, c0[0] + c1[0], c0[1] + c1[1]);
            sts64f(dst + 256, c0[2] + c1[2], c0[3] + c1[3]);
        }
        if (tid == 0 && is_q) STAMP(47);
        if (tid == 224 && is_q) STAMP(48);
        cbar();
        if (tid == 0 && is_q) STAMP(49);
        if (tid == 0 && !dry) {
            if (st == 0) {
                mbar_arrive_n(bars + 8 * (BAR_EMPTY + 3), 4); mbar_arrive_n(bars + 8 * (BAR_EMPTY + 4), 4);
                if (!has_mod) mbar_arrive_n(bars + 8 * (BAR_EMPTY + 5), 4);
            } else {
                mbar_arrive_n(bars + 8 * (BAR_EMPTY + 5), 4); mbar_arrive_n(bars + 8 * (BAR_EMPTY + 6), 4);
                mbar_arrive_n(bars + 8 * (BAR_EMPTY + 7), 4);
            }
        }
        if (tid < 128) {
            const bool crit = !is_q && cta < 36;
            const int b = crit ? (tid >> 3) & 7 : tid >> 4, cp = crit ? tid & 7 : tid & 15;
            const uint32_t ra = red + (cp >> 3) * 512 + (2 * (cp & 7)) * 32 + b * 4;
            float v0 = (ldsf(ra) + ldsf(ra + 1024)) + (ldsf(ra + 2048) + ldsf(ra + 3072));
            float v1 = (ldsf(ra + 32) + ldsf(ra + 1056)) + (ldsf(ra + 2080) + ldsf(ra + 3104));
            u64* dst;
            if (crit) {
                const float ca0 = rbf((ldsf(ra + 512) + ldsf(ra + 1536)) + (ldsf(ra + 2560) + ldsf(ra + 3584)));
                const float ca1 = rbf((ldsf(ra + 544) + ldsf(ra + 1568)) + (ldsf(ra + 2592) + ldsf(ra + 3616)));
                const float mean = ldsf(stat + 8 * b), rstd = ldsf(stat + 8 * b + 4);
                v0 = (bf_lo(xpair) - mean) * rstd * (1.f + ca0) + rbf(v0);
                v1 = (bf_hi(xpair) - mean) * rstd * (1.f + ca1) + rbf(v1);
                dst = &scr->h0[b][8 * cta + cp];
            } else {
                dst = is_q ? &scr->q[grp][b][16 * mem + cp] : &scr->mod[b][16 * (cta - 36) + cp];
            }
            if (!dry && (!crit || tid < 64)) ll_st(dst, pack_bf16(v0, v1), tag);
        }
        if (tid == 0) STAMP(is_q ? 17 : 46);
    }
#pragma unroll 1
    for (int pass = DRY_T ? 0 : 1; pass < 2; pass++) {
    const bool live = DRY_T ? pass != 0 : true;
    cbar();
    PIN32(sb); PIN32(tid); PIN32(cta); PIN64(scr);
    const int warp = tid >> 5, lane = tid & 31, grp = cta >> 3, mem = cta & 7, g = lane >> 2, t = lane & 3;
    const uint32_t bars = sb + OFF_BAR, act = sb + OFF_ACT, actb = sb + OFF_ACTB, red = sb + OFF_RED;
    const uint32_t act_row = act + warp * ACT_PITCH;
    const int rb = grp >> 1;
    const int rpair = 36 * mem + 18 * (grp & 1) + (lane < 18 ? lane : 0);
    uint32_t x_r = 0, ga_r = 0, gb_r = 0;
    uint32_t sbv[9], cbv[9];
#pragma unroll
    for (int k = 0; k < 9; k++) sbv[k] = cbv[k] = 0;

    float oacc[8][4];
#pragma unroll
    for (int m = 0; m < 8; m++) { oacc[m][0] = oacc[m][1] = oacc[m][2] = oacc[m][3] = 0.f; }
    float m0 = -INFINITY, m1 = -INFINITY, l0 = 0.f, l1 = 0.f;
    const float SC = 0.08838834764831845f * 1.4426950408889634f;
    if (live) {
        uint32_t qf[16];
        ll_poll<16, 4>(&scr->q[grp][mem][(g & 1) * 64 + t], tag, qf);
        if (tid == 0) STAMP(5);
        const int gi = warp >> 2, wq = warp & 3;
        const uint32_t offK = (16 * wq + (lane & 7) + (((lane >> 3) & 1) << 3)) * 128;
        const uint32_t offV = (16 * wq + (lane & 7) + ((lane >> 4) << 3)) * 128;
        const uint32_t xK = ((lane >> 4) ^ (lane & 7)) << 4, xV = (((lane >> 3) & 1) ^ (lane & 7)) << 4;
        int tp = TILE0 + 2 * gi;
        int slot = tp % NSLOT, use = tp / NSLOT;
#pragma unroll 1
        for (int kb = gi; kb < NTILES / 2; kb += 2) {
            if (kb - gi == 16) {
                if (warp == 7) {
                    x_r = __ldg(reinterpret_cast<const uint32_t*>(prm.x + rb * DM) + rpair);
                    uint32_t gg[2];
                    ll_poll<2, 864>(&scr->mod[rb][rpair], tag, gg);
                    ga_r = gg[0]; gb_r = gg[1];
                }
                {
                    const u64* mp = &scr->mod[warp][288 + 3 * lane];
                    int it = 0;
                    uint32_t bad;
                    do {
                        bad = 0;
#pragma unroll
                        for (int k = 0; k < 9; k++) {
                            uint32_t t0, t1;
                            ll_ld(mp + 96 * (k / 3) + k % 3, sbv[k], t0);
                            ll_ld(mp + 288 + 96 * (k / 3) + k % 3, cbv[k], t1);
                            bad |= (t0 ^ tag) | (t1 ^ tag);
                        }
                    } while (!poll_done(bad, it));
                }
                if (tid < 128) ll_st(&scr->o[grp][mem][tid], 0, 0);
                if (tid < 144) ll_st(&scr->hh[grp][18 * mem][0] + tid, 0, 0);
                if (tid < 6) ll_st128(&scr->x1[rb][12 * mem + 6 * (grp & 1) + tid][0], 0, 0, 0, 0);
#pragma unroll 1
                for (int i = tid; i < 576; i += 256) {
                    const int kq = i / 36;
                    u64* pp = &scr->p1[mem][kq][grp][i - 36 * kq];
                    ll_st(pp, 0, 0); ll_st(pp + P2_MINUS_P1, 0, 0);
                }
            }
            const uint32_t kt = sb + slot * SLOT + offK;
            mbar_wait(bars + 8 * (BAR_FULL + slot), use & 1);
            float sa[4] = {0.f, 0.f, 0.f, 0.f}, sc2[4] = {0.f, 0.f, 0.f, 0.f};
#pragma unroll
            for (int ks = 0; ks < 8; ks++) {
                uint32_t a[4];
                ldsm4(a, kt + (ks >> 2) * 8192 + (xK ^ ((ks & 3) << 5)));
                if (ks & 1) mma16816(sc2, a, qf[2 * ks], qf[2 * ks + 1]); else mma16816(sa, a, qf[2 * ks], qf[2 * ks + 1]);
            }
            __syncwarp();
            if (lane == 0) mbar_arrive(bars + 8 * (BAR_EMPTY + slot));
            const float s0 = sa[0] + sc2[0], s1 = sa[1] + sc2[1], s2 = sa[2] + sc2[2], s3 = sa[3] + sc2[3];
            const bool grow = (s0 > m0) || (s2 > m0) || (s1 > m1) || (s3 > m1);
            if (__any_sync(0xffffffffu, grow)) {
                float n0 = fmaxf(s0, s2), n1 = fmaxf(s1, s3);
#pragma unroll
                for (int o = 4; o < 32; o <<= 1) {
                    n0 = fmaxf(n0, __shfl_xor_sync(0xffffffffu, n0, o));
                    n1 = fmaxf(n1, __shfl_xor_sync(0xffffffffu, n1, o));
                }
                n0 = fmaxf(n0, m0); n1 = fmaxf(n1, m1);
                const float a0 = ex2((m0 - n0) * SC), a1 = ex2((m1 - n1) * SC);
                m0 = n0; m1 = n1; l0 *= a0; l1 *= a1;
#pragma unroll
                for (int m = 0; m < 8; m++) { oacc[m][0] *= a0; oacc[m][1] *= a1; oacc[m][2] *= a0; oacc[m][3] *= a1; }
            }
            const float mc0 = m0 * SC, mc1 = m1 * SC;
            const float p0 = ex2(fmaf(s0, SC, -mc0)), p1 = ex2(fmaf(s1, SC, -mc1));
            const float p2 = ex2(fmaf(s2, SC, -mc0)), p3 = ex2(fmaf(s3, SC, -mc1));
            l0 += p0 + p2; l1 += p1 + p3;
            const uint32_t pb0 = movmat(pack_bf16(p0, p1)), pb1 = movmat(pack_bf16(p2, p3));
            const uint32_t vt = sb + (slot + 1) * SLOT + offV;
            mbar_wait(bars + 8 * (BAR_FULL + slot + 1), use & 1);
#pragma unroll
            for (int mt = 0; mt < 8; mt++) {
                uint32_t a[4];
                ldsm4t(a, vt + (mt >> 2) * 8192 + (xV ^ ((mt & 3) << 5)));
                mma16816(oacc[mt], a, pb0, pb1);
            }
            __syncwarp();
            if (lane == 0) mbar_arrive(bars + 8 * (BAR_EMPTY + slot + 1));
            tp += 4;
            if (tp < PH2 + 4) { slot += 4; if (slot >= NSLOT) { slot -= NSLOT; use++; } }
            else use++;
        }
    }
    if (tid == 0) STAMP(6);
    if (tid == 128) STAMP(26);

    {
#pragma unroll
        for (int o = 4; o < 32; o <<= 1) { l0 += __shfl_xor_sync(0xffffffffu, l0, o); l1 += __shfl_xor_sync(0xffffffffu, l1, o); }
        const uint32_t ro = red + warp * 1024 + g * 8;
#pragma unroll
        for (int mt = 0; mt < 8; mt++) {
            if (t == (mt >> 1)) {
                sts64f(ro + mt * 128, oacc[mt][0], oacc[mt][1]);
                sts64f(ro + mt * 128 + 64, oacc[mt][2], oacc[mt][3]);
            }
        }
        if (lane == 0) sts128f(red + 8192 + warp * 16, m0, m1, l0, l1);
        u64* po = &scr->o[grp][mem][tid & 127];
        uint32_t rv = red + (tid & 63) * 16;
        PIN64(po); PIN32(rv);
        cbar();
        if (tid < 128) {
            const bool h = tid >= 64;
            float mw[8], lw[8], v0[8], v1[8];
#pragma unroll
            for (int w = 0; w < 8; w++) {
                const float4 a = lds128f(red + 8192 + w * 16), v = lds128f(rv + w * 1024);
                mw[w] = h ? a.y : a.x; lw[w] = h ? a.w : a.z;
                v0[w] = h ? v.y : v.x; v1[w] = h ? v.w : v.z;
            }
            const float M = fmaxf(fmaxf(fmaxf(mw[0], mw[1]), fmaxf(mw[2], mw[3])), fmaxf(fmaxf(mw[4], mw[5]), fmaxf(mw[6], mw[7])));
            float L = 0.f, o0 = 0.f, o1 = 0.f;
#pragma unroll
            for (int w = 0; w < 8; w++) {
                const float f = ex2((mw[w] - M) * SC);
                L = fmaf(f, lw[w], L); o0 = fmaf(f, v0[w], o0); o1 = fmaf(f, v1[w], o1);
            }
            const float inv = __fdividef(1.f, L);
            if (live) ll_st(po, pack_bf16(o0 * inv, o1 * inv), tag);
        }
    }
    if (tid == 0) STAMP(7);
    const int rl = (lane & 7) + ((lane >> 4) << 3);
    const uint32_t a72 = sb + rl * 144 + (2 * warp + ((lane >> 3) & 1)) * 16;
    u64 *pw0, *pw1;
    {
        const int c0 = min(16 * warp + g, 71), c1 = min(16 * warp + g + 8, 71);
        u64* pb = &scr->p1[mem][4 * t][grp][0];
        pw0 = pb + (c0 >= 36 ? 576 + c0 - 36 : c0);
        pw1 = pb + (c1 >= 36 ? 576 + c1 - 36 : c1);
    }
    const bool hi_ok = warp < 4;
    {
        uint32_t wa[16][4];
        if (live) { mbar_wait(bars + 8 * (BAR_T + 0), 0); mbar_wait(bars + 8 * (BAR_T + 1), 0); }
        gemv72_load<16>(wa, a72 + T_WO);
        if (tid == 0) STAMP(18);
        const u64* po = &scr->o[grp][warp][lane];
        uint32_t dst = actb + warp * ACTB_O_PITCH + lane * 4;
        uint32_t baddr = actb + (lane & 7) * ACTB_O_PITCH + (lane >> 3) * 16;
        PIN64(pw0); PIN64(pw1); PIN32(dst); PIN32(baddr);
        uint32_t ov[4] = {0u, 0u, 0u, 0u};
        if (live) ll_poll<4, 32>(po, tag, ov);
        if (tid == 0) STAMP(53);
        if (tid == 128) STAMP(54);
        if (tid == 224) STAMP(55);
#pragma unroll
        for (int k = 0; k < 4; k++) sts32(dst + 128 * k, ov[k]);
        cbar();
        if (tid == 0) STAMP(8);
        if (warp < 5) gemv72_run<16>(wa, baddr, pw0, pw1, hi_ok, tag, live, sb, 52);
        if (tid == 0) STAMP(21);
    }
    uint32_t x1_r = 0;
    const u64* pr = &scr->p1[mem][grp][2 * warp][lane < 18 ? 2 * lane : 0];
    {
        u64* px = &scr->x1[rb][12 * mem + 6 * (grp & 1) + (lane < 6 ? lane : 0)][0];
        int src = lane < 6 ? 3 * lane : 0;
        PIN64(px); PIN32(src);
        float a0 = 0.f, a1 = 0.f;
        reduce16(pr, red, warp, lane, tag, live, a0, a1);
        if (warp == 7) {
            x1_r = pack_bf16(fmaf(bf_lo(ga_r), a0, bf_lo(x_r)), fmaf(bf_hi(ga_r), a1, bf_hi(x_r)));
            const uint32_t w0 = __shfl_sync(0xffffffffu, x1_r, src), w1 = __shfl_sync(0xffffffffu, x1_r, src + 1),
                           w2 = __shfl_sync(0xffffffffu, x1_r, src + 2);
            if (live && lane < 6) ll_st128(px, w0, w1, w2, tag);
            if (lane == 0) STAMP(9);
        }
    }
    {
        const int mat = warp >> 2, kg = warp & 3;
        if (live) {
#pragma unroll 1
            for (int p = 0; p < 3; p++) mbar_wait(bars + 8 * (BAR_T + 2 + 3 * mat + p), 0);
        }
        if (tid == 0) STAMP(19);
        const uint32_t aaddr = sb + (mat ? T_WU : T_WG) + (144 * kg + rl) * 80 + ((lane >> 3) & 1) * 16;
        uint32_t wa[9][3][4];
#pragma unroll
        for (int i = 0; i < 6; i++)
#pragma unroll
            for (int m = 0; m < 3; m++) ldsm4t(wa[i][m], aaddr + i * 16 * 80 + m * 32);

        const u64* xp = &scr->x1[warp][lane][0];
        uint32_t adst = act_row + 12 * lane;
        uint32_t baddr = act + (lane & 7) * ACT_PITCH + (lane >> 3) * 16 + 288 * kg;
        PIN32(adst); PIN32(baddr);
        uint32_t xv[9] = {0u, 0u, 0u, 0u, 0u, 0u, 0u, 0u, 0u};
        if (live) {
            int it = 0;
            uint32_t bad;
            do {
                bad = 0;
#pragma unroll
                for (int k = 0; k < 3; k++) {
                    uint32_t tg;
                    ll_ld128(xp + 64 * k, xv[3 * k], xv[3 * k + 1], xv[3 * k + 2], tg);
                    bad |= tg ^ tag;
                }
            } while (!poll_done(bad, it));
        }
        if (tid == 0) STAMP(23);
        float mean, rstd;
        ln_stats(xv, mean, rstd);
#pragma unroll
        for (int k = 0; k < 9; k++) {
            const float h0 = (bf_lo(xv[k]) - mean) * rstd * (1.f + bf_lo(cbv[k])) + bf_lo(sbv[k]);
            const float h1 = (bf_hi(xv[k]) - mean) * rstd * (1.f + bf_hi(cbv[k])) + bf_hi(sbv[k]);
            sts32(adst + 384 * (k / 3) + 4 * (k % 3), pack_bf16(h0, h1));
        }
#pragma unroll
        for (int i = 6; i < 9; i++)
#pragma unroll
            for (int m = 0; m < 3; m++) ldsm4t(wa[i][m], aaddr + i * 16 * 80 + m * 32);
        uint32_t rdst = red + warp * 1536 + g * 32 + t * 8;
        uint32_t rsrc = red + (((36 * cta) & 7) + 2 * (tid >> 3)) * 32 + (tid & 7) * 4;
        u64* ph = &scr->hh[grp][18 * mem][0] + (tid < 144 ? tid : 0);
        PIN32(rdst); PIN32(rsrc); PIN64(ph);
        cbar();
        if (tid == 0) STAMP(10);
        float c[2][3][4];
#pragma unroll
        for (int m = 0; m < 3; m++)
#pragma unroll
            for (int j = 0; j < 4; j++) c[0][m][j] = c[1][m][j] = 0.f;
#pragma unroll
        for (int i = 0; i < 9; i += 2) {
            uint32_t b[4];
            ldsm4(b, baddr + i * 32);
#pragma unroll
            for (int m = 0; m < 3; m++) {
                mma16816(c[0][m], wa[i][m], b[0], b[1]);
                if (i + 1 < 9) mma16816(c[1][m], wa[i + 1][m], b[2], b[3]);
            }
        }
#pragma unroll
        for (int m = 0; m < 3; m++) {
            sts64f(rdst + m * 512, c[0][m][0] + c[1][m][0], c[0][m][1] + c[1][m][1]);
            sts64f(rdst + m * 512 + 256, c[0][m][2] + c[1][m][2], c[0][m][3] + c[1][m][3]);
        }
        if (tid == 0) STAMP(24);
        cbar();
        if (tid < 144) {
            float r[2];
#pragma unroll
            for (int e = 0; e < 2; e++) {
                const uint32_t a = rsrc + 32 * e;
                const float gg = (ldsf(a) + ldsf(a + 1536)) + (ldsf(a + 3072) + ldsf(a + 4608));
                const float uu = (ldsf(a + 6144) + ldsf(a + 7680)) + (ldsf(a + 9216) + ldsf(a + 10752));
                r[e] = gelu_f(gg) * uu;
            }
            if (live) ll_st(ph, pack_bf16(r[0], r[1]), tag);
        }
        if (live && cta == 0 && tid == 255) {
            asm volatile("st.relaxed.gpu.global.u32 [%0], %1;" ::"l"(&scr->epoch), "r"(tag) : "memory");
            asm volatile("st.relaxed.gpu.global.u32 [%0], %1;" ::"l"(&scr->prog), "r"(0u) : "memory");
        }
    }
    if (tid == 0) STAMP(11);
    {
        uint32_t wa[18][4];
        if (live) {
#pragma unroll 1
            for (int p = 0; p < 3; p++) mbar_wait(bars + 8 * (BAR_T + 8 + p), 0);
        }
        gemv72_load<18>(wa, a72 + T_WD);
        if (tid == 0) STAMP(20);
        const u64* hp = &scr->hh[grp][0][0] + tid;
        const u64* hl = &scr->hh[grp][128][0] + (tid & 127);
        uint32_t dst = actb + (tid & 7) * ACTB_H_PITCH + (tid >> 3) * 4;
        uint32_t dl = actb + (tid & 7) * ACTB_H_PITCH + (128 + ((tid & 127) >> 3)) * 4;
        uint32_t baddr = actb + (lane & 7) * ACTB_H_PITCH + (lane >> 3) * 16;
        u64 *q0 = pw0 + P2_MINUS_P1, *q1 = pw1 + P2_MINUS_P1;
        PIN32(dst); PIN32(dl); PIN32(baddr); PIN64(q0); PIN64(q1);
        uint32_t hv[5] = {0u, 0u, 0u, 0u, 0u};
        if (live) {
            int it = 0;
            uint32_t bad;
            do {
                bad = 0;
#pragma unroll
                for (int k = 0; k < 5; k++) { uint32_t tg; ll_ld(k < 4 ? hp + 256 * k : hl, hv[k], tg); bad |= tg ^ tag; }
            } while (!poll_done(bad, it));
        }
#pragma unroll
        for (int k = 0; k < 4; k++) sts32(dst + 128 * k, hv[k]);
        sts32(dl, hv[4]);
        cbar();
        if (tid == 0) STAMP(12);
        if (warp < 5) gemv72_run<18>(wa, baddr, q0, q1, hi_ok, tag, live);
        if (tid == 0) STAMP(22);
    }
    {
        uint32_t* po = reinterpret_cast<uint32_t*>(prm.out + rb * DM) + rpair;
        PIN64(po);
        float a0 = 0.f, a1 = 0.f;
        reduce16(pr + P2_MINUS_P1, red, warp, lane, tag, live, a0, a1);
        if (warp == 7) {
            if (live && lane < 18) *po = pack_bf16(fmaf(bf_lo(gb_r), a0, bf_lo(x1_r)), fmaf(bf_hi(gb_r), a1, bf_hi(x1_r)));
            if (lane == 0) STAMP(13);
        }
    }
    }
}

typedef CUresult (*EncodeFn)(CUtensorMap*, CUtensorMapDataType, cuuint32_t, void*, const cuuint64_t*, const cuuint64_t*,
                             const cuuint32_t*, const cuuint32_t*, CUtensorMapInterleave, CUtensorMapSwizzle,
                             CUtensorMapL2promotion, CUtensorMapFloatOOBfill);

void make_map2d(EncodeFn enc, CUtensorMap* m, const void* ptr, uint64_t cols, uint64_t rows, uint32_t bc, uint32_t br,
                CUtensorMapSwizzle sw, CUtensorMapL2promotion pr) {
    cuuint64_t dims[2] = {cols, rows};
    cuuint64_t strides[1] = {cols * 2};
    cuuint32_t box[2] = {bc, br};
    cuuint32_t es[2] = {1, 1};
    enc(m, CU_TENSOR_MAP_DATA_TYPE_BFLOAT16, 2, const_cast<void*>(ptr), dims, strides, box, es,
        CU_TENSOR_MAP_INTERLEAVE_NONE, sw, pr, CU_TENSOR_MAP_FLOAT_OOB_FILL_NONE);
}
void make_map_kv(EncodeFn enc, CUtensorMap* m, const void* ptr) {
    cuuint64_t dims[3] = {64, (cuuint64_t)NB * 16 * SK, 2};
    cuuint64_t strides[2] = {256, 128};
    cuuint32_t box[3] = {64, 64, 2};
    cuuint32_t es[3] = {1, 1, 1};
    enc(m, CU_TENSOR_MAP_DATA_TYPE_BFLOAT16, 3, const_cast<void*>(ptr), dims, strides, box, es,
        CU_TENSOR_MAP_INTERLEAVE_NONE, CU_TENSOR_MAP_SWIZZLE_128B, CU_TENSOR_MAP_L2_PROMOTION_L2_256B,
        CU_TENSOR_MAP_FLOAT_OOB_FILL_NONE);
}

}

extern "C" void kernel_launch(void* const* d_in, const int* in_sizes, int n_in, void* d_out, int out_size) {
    (void)in_sizes; (void)n_in; (void)out_size;
    static EncodeFn enc = nullptr;
    static Scratch* scr = nullptr;
    if (!enc) {
        void* fn = nullptr;
        cudaDriverEntryPointQueryResult qr;
        cudaGetDriverEntryPoint("cuTensorMapEncodeTiled", &fn, cudaEnableDefault, &qr);
        enc = (EncodeFn)fn;
        cudaGetSymbolAddress((void**)&scr, g_scr);
        cudaFuncSetAttribute(adaln_gqa_geglu_decode_kernel, cudaFuncAttributeMaxDynamicSharedMemorySize, SMEM_BYTES);
    }
    CUtensorMap tmK, tmV, tmMod, tmWq, tmWo, tmWg, tmWu, tmWd;
    make_map_kv(enc, &tmK, d_in[1]);
    make_map_kv(enc, &tmV, d_in[2]);
    make_map2d(enc, &tmMod, d_in[10], 6 * DM, DM, 32, 192, CU_TENSOR_MAP_SWIZZLE_64B, CU_TENSOR_MAP_L2_PROMOTION_L2_128B);
    make_map2d(enc, &tmWq, d_in[3], 4096, DM, 32, 192, CU_TENSOR_MAP_SWIZZLE_64B, CU_TENSOR_MAP_L2_PROMOTION_L2_128B);
    make_map2d(enc, &tmWo, d_in[4], DM, 4096, 72, 128, CU_TENSOR_MAP_SWIZZLE_NONE, CU_TENSOR_MAP_L2_PROMOTION_L2_128B);
    make_map2d(enc, &tmWg, d_in[6], DF, DM, 40, 192, CU_TENSOR_MAP_SWIZZLE_NONE, CU_TENSOR_MAP_L2_PROMOTION_L2_128B);
    make_map2d(enc, &tmWu, d_in[7], DF, DM, 40, 192, CU_TENSOR_MAP_SWIZZLE_NONE, CU_TENSOR_MAP_L2_PROMOTION_L2_128B);
    make_map2d(enc, &tmWd, d_in[8], DM, DF, 72, 96, CU_TENSOR_MAP_SWIZZLE_NONE, CU_TENSOR_MAP_L2_PROMOTION_L2_128B);
    Params prm;
    prm.x = (const __nv_bfloat16*)d_in[0];
    prm.c = (const __nv_bfloat16*)d_in[9];
    prm.wmod = (const __nv_bfloat16*)d_in[10];
    prm.k = (const __nv_bfloat16*)d_in[1];
    prm.v = (const __nv_bfloat16*)d_in[2];
    prm.out = (__nv_bfloat16*)d_out;
    prm.scr = scr;
    adaln_gqa_geglu_decode_kernel<<<NCTA, NTHREADS, SMEM_BYTES, cudaStreamPerThread>>>(prm, tmK, tmV, tmMod, tmWq, tmWo, tmWg, tmWu, tmWd);
}
```

```cpp
#include <cuda_runtime.h>
#include <cuda_bf16.h>
#include <cuda.h>
#include <stdint.h>
#include <stddef.h>

namespace {

typedef unsigned long long u64;

constexpr int NB = 8;
constexpr int DM = 576;
constexpr int SK = 8192;
constexpr int DF = 4608;
constexpr int NCTA = 128;
constexpr int NTHREADS = 288;

constexpr int NSLOT = 12;
constexpr int SLOT = 16384;
constexpr int RING = NSLOT * SLOT;
constexpr int P_REG = DM * 64;
constexpr int P_A = 3 * SLOT;
constexpr int P_B = P_A + P_REG;
constexpr int T_WO = 0;
constexpr int T_WG = T_WO + 256 * 144;
constexpr int T_WU = T_WG + DM * 80;
constexpr int T_WD = T_WU + DM * 80;
constexpr int T_END = T_WD + 288 * 144;
static_assert(T_END <= RING, "tail overlay");
static_assert(P_B + P_REG <= 8 * SLOT, "prologue overlay");
constexpr int ACT_PITCH = 1168;
constexpr int OFF_ACT = RING;
constexpr int OFF_RED = OFF_ACT + NB * ACT_PITCH;
constexpr int RED_BYTES = 12288 + 256;
constexpr int ACTB_O_PITCH = 528;
constexpr int ACTB_H_PITCH = 592;
constexpr int OFF_ACTB = OFF_RED + RED_BYTES;
constexpr int OFF_STAT = OFF_ACTB + NB * ACTB_H_PITCH;
constexpr int OFF_BAR = OFF_STAT + 128;
constexpr int BAR_FULL = 0, BAR_EMPTY = NSLOT, BAR_P = 2 * NSLOT, BAR_T = BAR_P + 6;
constexpr int NT_PIECES = 11;
constexpr int BAR_CRIT = BAR_T + NT_PIECES;
constexpr int NBARS = BAR_CRIT + 1;
constexpr int OFF_Q = OFF_BAR + NBARS * 8;
constexpr int OFF_STAMP = OFF_Q + 16 * 8;
constexpr int SMEM_USED = OFF_STAMP + 64 * 8;
constexpr int SMEM_BYTES = SMEM_USED + 1024;
static_assert(SMEM_BYTES <= 232448, "smem");

constexpr int NTILES = 256;
constexpr int TILE0 = 8;
constexpr int TILE_END = TILE0 + NTILES;

#define PACE_D0 4
#define PACE_GAIN 6
#define PACE_DMIN 3
#define PACE_DMAX 8
#define PACE_DSTART 3
#define WIN_P 45056
#define START_TILES 2
#define WIN_T 49152
#define NEARLY 0

#define CRIT_FIRST 0
#define PF_TILES 0
constexpr int PH2 = NEARLY > 0 ? 248 : 1000;
#define DRY_P 0
#define DRY_T 0
#define PREFETCH_TM 1
constexpr int SPIN_LIMIT = 1 << 22;

struct Scratch {
    u64 h0[NB][288];
    u64 mod[NB][1152];
    u64 q[16][NB][128];
    u64 o[16][NB][128];
    u64 p1[8][16][16][36];
    u64 x1[NB][96][2];
    u64 hh[16][144][NB];
    u64 p2[8][16][16][36];
    unsigned int epoch, pad0[31];
    unsigned int prog, pad1[31];
};
__device__ __align__(1024) Scratch g_scr;
constexpr int P2_MINUS_P1 = (int)((offsetof(Scratch, p2) - offsetof(Scratch, p1)) / 8);

#define PIN32(x) asm volatile("" : "+r"(x))
#define PIN64(x) asm volatile("" : "+l"(x))

__device__ __forceinline__ uint32_t smem_u32(const void* p) { return (uint32_t)__cvta_generic_to_shared(p); }
__device__ __forceinline__ void sts32(uint32_t a, uint32_t v) { asm volatile("st.shared.b32 [%0], %1;" ::"r"(a), "r"(v) : "memory"); }
__device__ __forceinline__ void sts64f(uint32_t a, float x, float y) { asm volatile("st.shared.v2.f32 [%0], {%1, %2};" ::"r"(a), "f"(x), "f"(y) : "memory"); }
__device__ __forceinline__ void sts128f(uint32_t a, float x, float y, float z, float w) {
    asm volatile("st.shared.v4.f32 [%0], {%1, %2, %3, %4};" ::"r"(a), "f"(x), "f"(y), "f"(z), "f"(w) : "memory");
}
__device__ __forceinline__ uint32_t lds32(uint32_t a) { uint32_t v; asm volatile("ld.shared.b32 %0, [%1];" : "=r"(v) : "r"(a)); return v; }
__device__ __forceinline__ float ldsf(uint32_t a) { float v; asm volatile("ld.shared.f32 %0, [%1];" : "=f"(v) : "r"(a)); return v; }
__device__ __forceinline__ float4 lds128f(uint32_t a) {
    float4 v;
    asm volatile("ld.shared.v4.f32 {%0, %1, %2, %3}, [%4];" : "=f"(v.x), "=f"(v.y), "=f"(v.z), "=f"(v.w) : "r"(a));
    return v;
}

#define STAMP(i) do {} while (0)

__device__ __forceinline__ void mbar_init(uint32_t bar, uint32_t cnt) {
    asm volatile("mbarrier.init.shared::cta.b64 [%0], %1;" ::"r"(bar), "r"(cnt) : "memory");
}
__device__ __forceinline__ void mbar_expect_tx(uint32_t bar, uint32_t bytes) {
    asm volatile("mbarrier.arrive.expect_tx.shared::cta.b64 _, [%0], %1;" ::"r"(bar), "r"(bytes) : "memory");
}
__device__ __forceinline__ void mbar_arrive(uint32_t bar) {
    asm volatile("mbarrier.arrive.shared::cta.b64 _, [%0];" ::"r"(bar) : "memory");
}
__device__ __forceinline__ void mbar_arrive_n(uint32_t bar, uint32_t n) {
    asm volatile("mbarrier.arrive.shared::cta.b64 _, [%0], %1;" ::"r"(bar), "r"(n) : "memory");
}
__device__ __forceinline__ void mbar_wait(uint32_t bar, uint32_t parity) {
    asm volatile(
        "{\n.reg .pred p;\n.reg .u32 n;\nmov.u32 n, 0;\n"
        "W: mbarrier.try_wait.parity.shared::cta.b64 p, [%0], %1;\n"
        "@p bra D;\nadd.u32 n, n, 1;\nsetp.lt.u32 p, n, %2;\n@p bra W;\ntrap;\nD:\n}"
        ::"r"(bar), "r"(parity), "n"(SPIN_LIMIT) : "memory");
}
__device__ __forceinline__ void cbar() { asm volatile("bar.sync 1, 256;" ::: "memory"); }

__device__ __forceinline__ void tma2d(uint32_t dst, const CUtensorMap* tm, int c0, int c1, uint32_t bar) {
    asm volatile("cp.async.bulk.tensor.2d.shared::cluster.global.mbarrier::complete_tx::bytes [%0], [%1, {%3, %4}], [%2];"
                 ::"r"(dst), "l"(tm), "r"(bar), "r"(c0), "r"(c1) : "memory");
}
__device__ __forceinline__ void tma3d_hint(uint32_t dst, const CUtensorMap* tm, int c0, int c1, int c2, uint32_t bar, uint64_t pol) {
    asm volatile("cp.async.bulk.tensor.3d.shared::cluster.global.mbarrier::complete_tx::bytes.L2::cache_hint [%0], [%1, {%3, %4, %5}], [%2], %6;"
                 ::"r"(dst), "l"(tm), "r"(bar), "r"(c0), "r"(c1), "r"(c2), "l"(pol) : "memory");
}
__device__ __forceinline__ void ldsm4(uint32_t (&r)[4], uint32_t a) {
    asm volatile("ldmatrix.sync.aligned.m8n8.x4.shared.b16 {%0,%1,%2,%3}, [%4];"
                 : "=r"(r[0]), "=r"(r[1]), "=r"(r[2]), "=r"(r[3]) : "r"(a));
}
__device__ __forceinline__ void ldsm4t(uint32_t (&r)[4], uint32_t a) {
    asm volatile("ldmatrix.sync.aligned.m8n8.x4.trans.shared.b16 {%0,%1,%2,%3}, [%4];"
                 : "=r"(r[0]), "=r"(r[1]), "=r"(r[2]), "=r"(r[3]) : "r"(a));
}
__device__ __forceinline__ void ldsm2(uint32_t& r0, uint32_t& r1, uint32_t a) {
    asm volatile("ldmatrix.sync.aligned.m8n8.x2.shared.b16 {%0,%1}, [%2];" : "=r"(r0), "=r"(r1) : "r"(a));
}
__device__ __forceinline__ void mma16816(float (&c)[4], const uint32_t (&a)[4], uint32_t b0, uint32_t b1) {
    asm volatile("mma.sync.aligned.m16n8k16.row.col.f32.bf16.bf16.f32 {%0,%1,%2,%3}, {%4,%5,%6,%7}, {%8,%9}, {%0,%1,%2,%3};"
                 : "+f"(c[0]), "+f"(c[1]), "+f"(c[2]), "+f"(c[3])
                 : "r"(a[0]), "r"(a[1]), "r"(a[2]), "r"(a[3]), "r"(b0), "r"(b1));
}
__device__ __forceinline__ uint32_t movmat(uint32_t a) {
    uint32_t d;
    asm volatile("movmatrix.sync.aligned.m8n8.trans.b16 %0, %1;" : "=r"(d) : "r"(a));
    return d;
}
__device__ __forceinline__ float ex2(float x) {
    float y;
    asm("ex2.approx.ftz.f32 %0, %1;" : "=f"(y) : "f"(x));
    return y;
}
__device__ __forceinline__ uint32_t pack_bf16(float lo, float hi) {
    __nv_bfloat162 v = __floats2bfloat162_rn(lo, hi);
    return *reinterpret_cast<uint32_t*>(&v);
}
__device__ __forceinline__ float bf_lo(uint32_t v) { return __uint_as_float(v << 16); }
__device__ __forceinline__ float bf_hi(uint32_t v) { return __uint_as_float(v & 0xffff0000u); }
__device__ __forceinline__ float rbf(float x) { return __bfloat162float(__float2bfloat16_rn(x)); }

__device__ __forceinline__ void ll_st(u64* p, uint32_t data, uint32_t tag) {
    asm volatile("{\n.reg .b64 v;\nmov.b64 v, {%1, %2};\nst.relaxed.gpu.global.b64 [%0], v;\n}" ::"l"(p), "r"(data), "r"(tag) : "memory");
}
__device__ __forceinline__ void ll_ld(const u64* p, uint32_t& data, uint32_t& tg) {
    asm volatile("{\n.reg .b64 v;\nld.relaxed.gpu.global.b64 v, [%2];\nmov.b64 {%0, %1}, v;\n}" : "=r"(data), "=r"(tg) : "l"(p) : "memory");
}
__device__ __forceinline__ void ll_ld2(const u64* p, uint32_t& d0, uint32_t& t0, uint32_t& d1, uint32_t& t1) {
    asm volatile("{\n.reg .b64 a, b;\nld.relaxed.gpu.global.v2.b64 {a, b}, [%4];\nmov.b64 {%0, %1}, a;\nmov.b64 {%2, %3}, b;\n}"
                 : "=r"(d0), "=r"(t0), "=r"(d1), "=r"(t1) : "l"(p) : "memory");
}
__device__ __forceinline__ void ll_st128(u64* p, uint32_t w0, uint32_t w1, uint32_t w2, uint32_t tag) {
    asm volatile("{\n.reg .b128 r;\n.reg .b64 lo, hi;\nmov.b64 lo, {%1, %2};\nmov.b64 hi, {%3, %4};\nmov.b128 r, {lo, hi};\n"
                 "st.relaxed.gpu.global.b128 [%0], r;\n}" ::"l"(p), "r"(w0), "r"(w1), "r"(w2), "r"(tag) : "memory");
}
__device__ __forceinline__ void ll_ld128(const u64* p, uint32_t& w0, uint32_t& w1, uint32_t& w2, uint32_t& tg) {
    asm volatile("{\n.reg .b128 r;\n.reg .b64 lo, hi;\nld.relaxed.gpu.global.b128 r, [%4];\nmov.b128 {lo, hi}, r;\n"
                 "mov.b64 {%0, %1}, lo;\nmov.b64 {%2, %3}, hi;\n}" : "=r"(w0), "=r"(w1), "=r"(w2), "=r"(tg) : "l"(p) : "memory");
}
__device__ __forceinline__ bool poll_done(uint32_t bad, int& it) {
    if (!__any_sync(0xffffffffu, bad != 0)) return true;
    if (++it > SPIN_LIMIT) __trap();
    return false;
}
template <int N, int STRIDE>
__device__ __forceinline__ void ll_poll(const u64* p, uint32_t tag, uint32_t (&out)[N]) {
    int it = 0;
    uint32_t bad;
    do {
        bad = 0;
#pragma unroll
        for (int i = 0; i < N; i++) { uint32_t tg; ll_ld(p + i * STRIDE, out[i], tg); bad |= tg ^ tag; }
    } while (!poll_done(bad, it));
}
__device__ __forceinline__ void reduce16(const u64* p, uint32_t buf, int warp, int lane, uint32_t tag, bool live, float& s0, float& s1) {
    uint32_t a0 = 0, a1 = 0, b0 = 0, b1 = 0;
    if (live) {
        int it = 0;
        uint32_t bad;
        do {
            uint32_t t0, t1, t2, t3;
            ll_ld2(p, a0, t0, a1, t1);
            ll_ld2(p + 36, b0, t2, b1, t3);
            bad = ((t0 ^ tag) | (t1 ^ tag)) | ((t2 ^ tag) | (t3 ^ tag));
        } while (!poll_done(bad, it));
    }
    if (lane < 18) sts64f(buf + (warp * 18 + lane) * 8, __uint_as_float(a0) + __uint_as_float(b0), __uint_as_float(a1) + __uint_as_float(b1));
    if (warp != 7) {
        asm volatile("bar.arrive 3, 256;" ::: "memory");
    } else {
        asm volatile("bar.sync 3, 256;" ::: "memory");
        float x[8], y[8];
        const uint32_t q = buf + (lane < 18 ? lane : 0) * 8;
#pragma unroll
        for (int w = 0; w < 8; w++) asm volatile("ld.shared.v2.f32 {%0, %1}, [%2];" : "=f"(x[w]), "=f"(y[w]) : "r"(q + w * 144));
        s0 = ((x[0] + x[1]) + (x[2] + x[3])) + ((x[4] + x[5]) + (x[6] + x[7]));
        s1 = ((y[0] + y[1]) + (y[2] + y[3])) + ((y[4] + y[5]) + (y[6] + y[7]));
    }
}

__device__ __forceinline__ void ln_stats(const uint32_t (&v)[9], float& mean, float& den) {
    const float k = __shfl_sync(0xffffffffu, bf_lo(v[0]), 0);
    float s = 0.f, q = 0.f;
#pragma unroll
    for (int i = 0; i < 9; i++) {
        const float a = bf_lo(v[i]) - k, b = bf_hi(v[i]) - k;
        s += a + b;
        q = fmaf(a, a, fmaf(b, b, q));
    }
#pragma unroll
    for (int o = 16; o > 0; o >>= 1) { s += __shfl_xor_sync(0xffffffffu, s, o); q += __shfl_xor_sync(0xffffffffu, q, o); }
    const float md = s * (1.0f / DM);
    mean = rbf(k + md);
    den = rbf(__fsqrt_rn(rbf(rbf(fmaxf(q * (1.0f / DM) - md * md, 0.f)) + 1e-5f)));
}
__device__ __forceinline__ uint32_t bf2_add(uint32_t a, uint32_t b) {
    uint32_t d; asm("add.rn.bf16x2 %0, %1, %2;" : "=r"(d) : "r"(a), "r"(b)); return d;
}
__device__ __forceinline__ uint32_t bf2_sub(uint32_t a, uint32_t b) {
    uint32_t d; asm("sub.rn.bf16x2 %0, %1, %2;" : "=r"(d) : "r"(a), "r"(b)); return d;
}
__device__ __forceinline__ uint32_t bf2_mul(uint32_t a, uint32_t b) {
    uint32_t d; asm("mul.rn.bf16x2 %0, %1, %2;" : "=r"(d) : "r"(a), "r"(b)); return d;
}
__device__ __forceinline__ uint32_t ln_mod2(uint32_t x, uint32_t m2, float rinv, uint32_t c1, uint32_t sh) {
    const uint32_t d = bf2_sub(x, m2);
    const uint32_t n = pack_bf16(bf_lo(d) * rinv, bf_hi(d) * rinv);
    return bf2_add(bf2_mul(n, c1), sh);
}
constexpr uint32_t BF2_ONE = 0x3f803f80u;
__device__ __forceinline__ float silu_f(float a) { return __fdividef(a, 1.f + __expf(-a)); }
__device__ __forceinline__ float gelu_f(float g) {
    const float z2 = 1.5957691216057308f * fmaf(0.044715f * g * g, g, g);
    return __fdividef(g, 1.f + __expf(-z2));
}

template <int KSTEPS>
__device__ __forceinline__ void gemv72_load(uint32_t (&a)[KSTEPS][4], uint32_t aaddr) {
#pragma unroll
    for (int i = 0; i < KSTEPS; i++) ldsm4t(a[i], aaddr + i * 16 * 144);
}
template <int KSTEPS>
__device__ __forceinline__ void gemv72_run(const uint32_t (&a)[KSTEPS][4], uint32_t baddr, u64* p0, u64* p1, bool hi_ok, uint32_t tag, bool live, uint32_t sb = 0, int st0 = -1) {
    float c[4][4];
#pragma unroll
    for (int j = 0; j < 4; j++) c[j][0] = c[j][1] = c[j][2] = c[j][3] = 0.f;
#pragma unroll
    for (int i = 0; i < KSTEPS; i += 2) {
        uint32_t b[4];
        ldsm4(b, baddr + i * 32);
        mma16816(c[i & 3], a[i], b[0], b[1]);
        mma16816(c[(i + 1) & 3], a[i + 1], b[2], b[3]);
    }
    const float r0 = (c[0][0] + c[1][0]) + (c[2][0] + c[3][0]), r1 = (c[0][1] + c[1][1]) + (c[2][1] + c[3][1]);
    const float r2 = (c[0][2] + c[1][2]) + (c[2][2] + c[3][2]), r3 = (c[0][3] + c[1][3]) + (c[2][3] + c[3][3]);
    if (live) { ll_st(p0, __float_as_uint(r0), tag); ll_st(p0 + 2 * 576, __float_as_uint(r1), tag); }
    if (live && hi_ok) { ll_st(p1, __float_as_uint(r2), tag); ll_st(p1 + 2 * 576, __float_as_uint(r3), tag); }
}

struct Params {
    const __nv_bfloat16* x;
    const __nv_bfloat16* c;
    const __nv_bfloat16* wmod;
    const __nv_bfloat16* k;
    const __nv_bfloat16* v;
    __nv_bfloat16* out;
    Scratch* scr;
};

__global__ void __launch_bounds__(NTHREADS, 1)
adaln_gqa_geglu_decode_kernel(const Params prm,
                              const __grid_constant__ CUtensorMap tmK, const __grid_constant__ CUtensorMap tmV,
                              const __grid_constant__ CUtensorMap tmMod, const __grid_constant__ CUtensorMap tmWq,
                              const __grid_constant__ CUtensorMap tmWo, const __grid_constant__ CUtensorMap tmWg,
                              const __grid_constant__ CUtensorMap tmWu, const __grid_constant__ CUtensorMap tmWd) {
    extern __shared__ unsigned char smem_raw[];
    uint32_t sb = (smem_u32(smem_raw) + 1023u) & ~1023u;
    int tid = threadIdx.x, cta = blockIdx.x;
    Scratch* scr = prm.scr;
    PIN32(sb); PIN32(tid); PIN32(cta); PIN64(scr);
    const uint32_t bars = sb + OFF_BAR;
    const int warp = tid >> 5, lane = tid & 31;
    const int grp = cta >> 3, mem = cta & 7;
    const bool has_mod = cta < 108;

    if (warp == 8) {
        if (lane >= 16 && lane < 16 + PF_TILES) {
            const int i = lane - 16;
            const __nv_bfloat16* src = ((i & 1) ? prm.v : prm.k) + ((size_t)(mem * 16 + grp) * SK + (i >> 1) * 64) * 128;
            uint64_t pol;
            asm volatile("createpolicy.fractional.L2::evict_first.b64 %0, 1.0;" : "=l"(pol));
            asm volatile("cp.async.bulk.prefetch.L2.global.L2::cache_hint [%0], %1, %2;" ::"l"(src), "r"(SLOT), "l"(pol) : "memory");
        }
        if (PREFETCH_TM && lane < 8) {
            const CUtensorMap* tm = lane == 0 ? &tmMod : lane == 1 ? &tmWq : lane == 2 ? &tmK : lane == 3 ? &tmV
                                  : lane == 4 ? &tmWo : lane == 5 ? &tmWg : lane == 6 ? &tmWu : &tmWd;
            asm volatile("prefetch.tensormap [%0];" ::"l"(tm) : "memory");
        }
        if (lane == 0) {
            STAMP(0);
        }
        if (lane == 0) {
#pragma unroll
            for (int s = 0; s < NBARS; s++) mbar_init(bars + 8 * s, (s >= BAR_EMPTY && s < BAR_P) ? 4 : 1);
#pragma unroll
            for (int s = 0; s < 8; s++) {
                mbar_arrive(bars + 8 * (BAR_FULL + s));
                if (s < 3 || (s >= 6 && !has_mod)) mbar_arrive_n(bars + 8 * (BAR_EMPTY + s), 4);
            }
            asm volatile("fence.mbarrier_init.release.cluster;" ::: "memory");
        }
        __syncwarp();
        if (lane == 0) STAMP(41);
        asm volatile("bar.arrive 2, 288;" ::: "memory");
        if (lane == 0) {
            uint64_t pol;
            asm volatile("createpolicy.fractional.L2::evict_first.b64 %0, 1.0;" : "=l"(pol));
            if (CRIT_FIRST && cta < 36) mbar_wait(bars + 8 * BAR_CRIT, 0);
            const uint32_t fifo = sb + OFF_Q;
            const int row0 = (mem * 16 + grp) * SK;
            const int boxcol = (36 * cta) & ~7;
            const int np = has_mod ? 6 : 3, np_first = cta < 36 ? 6 : 3;
            int head = 0, tail = 0, inflight = 0;
            int pi = cta < 36 ? 3 : 0, tp = TILE0, ti = 0, freed = 0, slot = TILE0, use = 0, win = PACE_DSTART, own_at = 0;
            unsigned gpend = 0;
            bool tdue = false;
#pragma unroll 1
            while (true) {
                uint32_t bar, par = 0;
                int bytes, window, kind;
                if (pi < np && (pi < np_first || tp >= TILE0 + START_TILES)) {
                    kind = 0; bar = bars + 8 * (BAR_P + pi); bytes = 12288;
                    window = pi < np_first ? (1 << 30) : WIN_P;
                } else if (tp < TILE_END && !tdue) {
                    kind = 1;
                    if (use > 0) mbar_wait(bars + 8 * (BAR_EMPTY + slot), (use - 1) & 1);
                    if (PACE_GAIN > 0 && (tp & 1) == 0) {
                        if (tp >= TILE0 + 12) {
                            const int sc = (own_at * NCTA - (int)gpend) * PACE_GAIN;
                            const int adj = sc >= 0 ? (sc + 2 * NCTA) / (4 * NCTA) : -((-sc + 2 * NCTA) / (4 * NCTA));
                            win = min(max(PACE_D0 - adj, PACE_DMIN), tp >= PH2 - 4 ? min(PACE_DMAX, 4) : PACE_DMAX);
                        }
                        asm volatile("red.relaxed.gpu.global.add.u32 [%0], 1;" ::"l"(&scr->prog) : "memory");
                        own_at = ((tp - TILE0) >> 1) + 1;
                        asm volatile("ld.relaxed.gpu.global.u32 %0, [%1];" : "=r"(gpend) : "l"(&scr->prog) : "memory");
                    } else if (PACE_GAIN == 0 && tp >= TILE0 + 12) win = PACE_D0;
                    bar = bars + 8 * (BAR_FULL + slot); par = use & 1; bytes = SLOT; window = tp < TILE0 + START_TILES ? (1 << 30) : win * SLOT;
                } else if (ti < NT_PIECES) {
                    kind = 2;
                    bytes = ti < 2 ? 18432 : ti < 8 ? 15360 : 13824;
                    const int end = ti < 2 ? 18432 * (ti + 1) : ti < 8 ? T_WG + 15360 * (ti - 1) : T_WD + 13824 * (ti - 7);
                    while (freed * SLOT < end) { mbar_wait(bars + 8 * (BAR_EMPTY + freed), (NEARLY > 0 && freed < 8) ? 0 : 1); freed++; }
                    bar = bars + 8 * (BAR_T + ti);
                    window = tp < TILE_END ? win * SLOT : WIN_T;
                } else break;
                while (head != tail && inflight + bytes > window) {
                    const uint32_t e = lds32(fifo + 8 * (head & 15));
                    mbar_wait(e & ~1u, e & 1u);
                    inflight -= (int)lds32(fifo + 8 * (head & 15) + 4);
                    head++;
                }
                sts32(fifo + 8 * (tail & 15), bar | par); sts32(fifo + 8 * (tail & 15) + 4, bytes);
                tail++; inflight += bytes;
                mbar_expect_tx(bar, bytes);
                if (kind == 0) {
                    const int r = pi >= 3 ? 1 : 0, pp = pi - 3 * r;
                    const bool is_q = (cta < 36) == (r == 1);
                    tma2d(sb + (r ? P_B : P_A) + pp * 12288, is_q ? &tmWq : &tmMod, is_q ? 32 * cta : 1152 + 32 * (cta - 36), 192 * pp, bar);
                    pi++;
                } else if (kind == 1) {
                    tma3d_hint(sb + slot * SLOT, (tp & 1) ? &tmV : &tmK, 0, row0 + ((tp - TILE0) >> 1) * 64, 0, bar, pol);
                    tdue = tp >= PH2 && (tp & 1) && ti < NEARLY;
                    if (++slot == NSLOT) { slot = tp < PH2 + 3 ? 0 : 8; use++; }
                    tp++;
                } else {
                    const CUtensorMap* tm = ti < 2 ? &tmWo : ti < 5 ? &tmWg : ti < 8 ? &tmWu : &tmWd;
                    const int off = ti < 2 ? 18432 * ti : ti < 8 ? T_WG + 15360 * (ti - 2) : T_WD + 13824 * (ti - 8);
                    const int c0 = (ti >= 2 && ti < 8) ? boxcol : 72 * mem;
                    const int c1 = ti < 2 ? 256 * grp + 128 * ti : ti < 5 ? 192 * (ti - 2) : ti < 8 ? 192 * (ti - 5) : 288 * grp + 96 * (ti - 8);
                    tma2d(sb + off, tm, c0, c1, bar);
                    ti++; tdue = false;
                }
            }
            STAMP(2);
        }
        return;
    }

    const int g = lane >> 2, t = lane & 3;
    const uint32_t act = sb + OFF_ACT, red = sb + OFF_RED, stat = sb + OFF_STAT;
    const uint32_t act_row = act + warp * ACT_PITCH;

    uint32_t xpair = 0;
    uint32_t cv[9];
    {
        unsigned ep = 0;
        if (tid == 0) asm volatile("ld.relaxed.gpu.global.u32 %0, [%1];" : "=r"(ep) : "l"(&scr->epoch) : "memory");
        if (cta < 36) {
            const int sub = tid & 3, row = tid >> 2;
            const char* src = reinterpret_cast<const char*>(prm.wmod) + row * (6 * DM * 2) + ((sub >> 1) * DM + 16 * cta) * 2 + (sub & 1) * 16;
            const uint32_t dst = sb + P_A + row * 64 + ((sub ^ ((row >> 1) & 3)) << 4);
#pragma unroll
            for (int j = 0; j < 9; j++)
                asm volatile("cp.async.cg.shared.global [%0], [%1], 16;" ::"r"(dst + j * 64 * 64), "l"(src + (size_t)j * 64 * (6 * DM * 2)) : "memory");
        }
        if (has_mod) {
            const uint32_t* crow = reinterpret_cast<const uint32_t*>(prm.c + warp * DM) + lane;
#pragma unroll
            for (int k = 0; k < 9; k++) cv[k] = __ldg(crow + 32 * k);
        }
        if (tid < 128) {
            ll_st(&scr->q[grp][tid >> 4][16 * mem + (tid & 15)], 0, 0);
            if (cta < 36) { if (tid < 64) ll_st(&scr->h0[tid >> 3][8 * cta + (tid & 7)], 0, 0); }
            else if (has_mod) ll_st(&scr->mod[tid >> 4][16 * (cta - 36) + (tid & 15)], 0, 0);
        }
        if (cta < 36) {
            const uint32_t* xrow = reinterpret_cast<const uint32_t*>(prm.x + warp * DM) + lane;
            uint32_t xv[9];
#pragma unroll
            for (int k = 0; k < 9; k++) xv[k] = __ldg(xrow + 32 * k);
            if (tid < 64) xpair = __ldg(reinterpret_cast<const uint32_t*>(prm.x + (tid >> 3) * DM + 16 * cta) + (tid & 7));
            float mean, den;
            ln_stats(xv, mean, den);
            if (lane == 0) sts64f(stat + 8 * warp, mean, den);
        }
        if (tid == 32) STAMP(44);
        if (tid == 0) sts32(stat + 64, ep + 1);
        if (tid == 0) STAMP(45);
    }
    asm volatile("bar.sync 2, 288;" ::: "memory");
    const uint32_t tag = lds32(stat + 64);
    if (tid == 0) STAMP(14);

    const int pass0 = (DRY_P && cta >= 36) ? -1 : 0;
#pragma unroll 1
    for (int pass = pass0; pass < 2; pass++) {
        const bool dry = pass < 0;
        const int st = dry ? 0 : pass;
        const bool is_q = (cta < 36) == (st == 1);
        if (!is_q && !has_mod) break;
        uint32_t av[9];
        if (!is_q && !dry) {
#pragma unroll
            for (int k = 0; k < 9; k++) av[k] = pack_bf16(silu_f(bf_lo(cv[k])), silu_f(bf_hi(cv[k])));
        }
        if (dry) {
#pragma unroll
            for (int k = 0; k < 9; k++) av[k] = 0;
        } else if (!is_q && cta < 36) {
            asm volatile("cp.async.wait_all;" ::: "memory");
        } else {
#pragma unroll 1
            for (int p = 0; p < 3; p++) mbar_wait(bars + 8 * (BAR_P + 3 * st + p), 0);
        }
        if (tid == 0) STAMP(15 + st);
        if (is_q && !dry) ll_poll<9, 32>(&scr->h0[warp][lane], tag, av);
        if (tid == 0 && is_q) STAMP(50);
        if (tid == 224 && is_q) STAMP(51);
        if (pass > pass0) cbar();
#pragma unroll
        for (int k = 0; k < 9; k++) sts32(act_row + 4 * (lane + 32 * k), av[k]);
        cbar();
        if (CRIT_FIRST && tid == 0 && !is_q && cta < 36) mbar_arrive(bars + 8 * BAR_CRIT);
        if (tid == 0) STAMP(is_q ? 4 : 3);
        {
            const int mt = warp & 1, kg = warp >> 1;
            const int rl = (lane & 7) + ((lane >> 4) << 3);
            const uint32_t aaddr = sb + (st ? P_B : P_A) + (144 * kg + rl) * 64 + (((2 * mt + ((lane >> 3) & 1)) ^ ((rl >> 1) & 3)) << 4);
            const uint32_t baddr = act + (lane & 7) * ACT_PITCH + ((lane >> 3) & 1) * 16 + 288 * kg;
            float c0[4] = {0.f, 0.f, 0.f, 0.f}, c1[4] = {0.f, 0.f, 0.f, 0.f};
#pragma unroll
            for (int i = 0; i < 9; i++) {
                uint32_t a[4], b0, b1;
                ldsm4t(a, aaddr + i * 16 * 64);
                ldsm2(b0, b1, baddr + i * 32);
                if (i & 1) mma16816(c1, a, b0, b1); else mma16816(c0, a, b0, b1);
            }
            const uint32_t dst = red + warp * 512 + g * 32 + t * 8;
            sts64f(dst, c0[0] + c1[0], c0[1] + c1[1]);
            sts64f(dst + 256, c0[2] + c1[2], c0[3] + c1[3]);
        }
        if (tid == 0 && is_q) STAMP(47);
        if (tid == 224 && is_q) STAMP(48);
        cbar();
        if (tid == 0 && is_q) STAMP(49);
        if (tid == 0 && !dry) {
            if (st == 0) {
                mbar_arrive_n(bars + 8 * (BAR_EMPTY + 3), 4); mbar_arrive_n(bars + 8 * (BAR_EMPTY + 4), 4);
                if (!has_mod) mbar_arrive_n(bars + 8 * (BAR_EMPTY + 5), 4);
            } else {
                mbar_arrive_n(bars + 8 * (BAR_EMPTY + 5), 4); mbar_arrive_n(bars + 8 * (BAR_EMPTY + 6), 4);
                mbar_arrive_n(bars + 8 * (BAR_EMPTY + 7), 4);
            }
        }
        if (tid < 128) {
            const bool crit = !is_q && cta < 36;
            const int b = crit ? (tid >> 3) & 7 : tid >> 4, cp = crit ? tid & 7 : tid & 15;
            const uint32_t ra = red + (cp >> 3) * 512 + (2 * (cp & 7)) * 32 + b * 4;
            const float v0 = (ldsf(ra) + ldsf(ra + 1024)) + (ldsf(ra + 2048) + ldsf(ra + 3072));
            const float v1 = (ldsf(ra + 32) + ldsf(ra + 1056)) + (ldsf(ra + 2080) + ldsf(ra + 3104));
            u64* dst;
            uint32_t val = pack_bf16(v0, v1);
            if (crit) {
                const uint32_t ca = pack_bf16((ldsf(ra + 512) + ldsf(ra + 1536)) + (ldsf(ra + 2560) + ldsf(ra + 3584)),
                                              (ldsf(ra + 544) + ldsf(ra + 1568)) + (ldsf(ra + 2592) + ldsf(ra + 3616)));
                const float mean = ldsf(stat + 8 * b), den = ldsf(stat + 8 * b + 4);
                const uint32_t d = bf2_sub(xpair, pack_bf16(mean, mean));
                const uint32_t n = pack_bf16(__fdiv_rn(bf_lo(d), den), __fdiv_rn(bf_hi(d), den));
                val = bf2_add(bf2_mul(n, bf2_add(BF2_ONE, ca)), val);
                dst = &scr->h0[b][8 * cta + cp];
            } else {
                dst = is_q ? &scr->q[grp][b][16 * mem + cp] : &scr->mod[b][16 * (cta - 36) + cp];
            }
            if (!dry && (!crit || tid < 64)) ll_st(dst, val, tag);
        }
        if (tid == 0) STAMP(is_q ? 17 : 46);
    }
#pragma unroll 1
    for (int pass = DRY_T ? 0 : 1; pass < 2; pass++) {
    const bool live = DRY_T ? pass != 0 : true;
    cbar();
    PIN32(sb); PIN32(tid); PIN32(cta); PIN64(scr);
    const int warp = tid >> 5, lane = tid & 31, grp = cta >> 3, mem = cta & 7, g = lane >> 2, t = lane & 3;
    const uint32_t bars = sb + OFF_BAR, act = sb + OFF_ACT, actb = sb + OFF_ACTB, red = sb + OFF_RED;
    const uint32_t act_row = act + warp * ACT_PITCH;
    const int rb = grp >> 1;
    const int rpair = 36 * mem + 18 * (grp & 1) + (lane < 18 ? lane : 0);
    uint32_t x_r = 0, ga_r = 0, gb_r = 0;
    uint32_t sbv[9], cbv[9];
#pragma unroll
    for (int k = 0; k < 9; k++) sbv[k] = cbv[k] = 0;

    float oacc[8][4];
#pragma unroll
    for (int m = 0; m < 8; m++) { oacc[m][0] = oacc[m][1] = oacc[m][2] = oacc[m][3] = 0.f; }
    float m0 = -INFINITY, m1 = -INFINITY, l0 = 0.f, l1 = 0.f;
    const float SC = 1.4426950408889634f;
    if (live) {
        uint32_t qf[16];
        ll_poll<16, 4>(&scr->q[grp][mem][(g & 1) * 64 + t], tag, qf);
        if (tid == 0) STAMP(5);
        const int gi = warp >> 2, wq = warp & 3;
        const uint32_t offK = (16 * wq + (lane & 7) + (((lane >> 3) & 1) << 3)) * 128;
        const uint32_t offV = (16 * wq + (lane & 7) + ((lane >> 4) << 3)) * 128;
        const uint32_t xK = ((lane >> 4) ^ (lane & 7)) << 4, xV = (((lane >> 3) & 1) ^ (lane & 7)) << 4;
        int tp = TILE0 + 2 * gi;
        int slot = tp % NSLOT, use = tp / NSLOT;
#pragma unroll 1
        for (int kb = gi; kb < NTILES / 2; kb += 2) {
            if (kb - gi == 16) {
                if (warp == 7) {
                    x_r = __ldg(reinterpret_cast<const uint32_t*>(prm.x + rb * DM) + rpair);
                    uint32_t gg[2];
                    ll_poll<2, 864>(&scr->mod[rb][rpair], tag, gg);
                    ga_r = gg[0]; gb_r = gg[1];
                }
                {
                    const u64* mp = &scr->mod[warp][288 + 3 * lane];
                    int it = 0;
                    uint32_t bad;
                    do {
                        bad = 0;
#pragma unroll
                        for (int k = 0; k < 9; k++) {
                            uint32_t t0, t1;
                            ll_ld(mp + 96 * (k / 3) + k % 3, sbv[k], t0);
                            ll_ld(mp + 288 + 96 * (k / 3) + k % 3, cbv[k], t1);
                            bad |= (t0 ^ tag) | (t1 ^ tag);
                        }
                    } while (!poll_done(bad, it));
#pragma unroll
                    for (int k = 0; k < 9; k++) cbv[k] = bf2_add(BF2_ONE, cbv[k]);
                }
                if (tid < 128) ll_st(&scr->o[grp][mem][tid], 0, 0);
                if (tid < 144) ll_st(&scr->hh[grp][18 * mem][0] + tid, 0, 0);
                if (tid < 6) ll_st128(&scr->x1[rb][12 * mem + 6 * (grp & 1) + tid][0], 0, 0, 0, 0);
#pragma unroll 1
                for (int i = tid; i < 576; i += 256) {
                    const int kq = i / 36;
                    u64* pp = &scr->p1[mem][kq][grp][i - 36 * kq];
                    ll_st(pp, 0, 0); ll_st(pp + P2_MINUS_P1, 0, 0);
                }
            }
            const uint32_t kt = sb + slot * SLOT + offK;
            mbar_wait(bars + 8 * (BAR_FULL + slot), use & 1);
            float sa[4] = {0.f, 0.f, 0.f, 0.f}, sc2[4] = {0.f, 0.f, 0.f, 0.f};
#pragma unroll
            for (int ks = 0; ks < 8; ks++) {
                uint32_t a[4];
                ldsm4(a, kt + (ks >> 2) * 8192 + (xK ^ ((ks & 3) << 5)));
                if (ks & 1) mma16816(sc2, a, qf[2 * ks], qf[2 * ks + 1]); else mma16816(sa, a, qf[2 * ks], qf[2 * ks + 1]);
            }
            __syncwarp();
            if (lane == 0) mbar_arrive(bars + 8 * (BAR_EMPTY + slot));
            const uint32_t r01 = pack_bf16(sa[0] + sc2[0], sa[1] + sc2[1]), r23 = pack_bf16(sa[2] + sc2[2], sa[3] + sc2[3]);
            const float RS = 0.08838834764831845f;
            const uint32_t u01 = pack_bf16(bf_lo(r01) * RS, bf_hi(r01) * RS), u23 = pack_bf16(bf_lo(r23) * RS, bf_hi(r23) * RS);
            const float s0 = bf_lo(u01), s1 = bf_hi(u01), s2 = bf_lo(u23), s3 = bf_hi(u23);
            const bool grow = (s0 > m0) || (s2 > m0) || (s1 > m1) || (s3 > m1);
            if (__any_sync(0xffffffffu, grow)) {
                float n0 = fmaxf(s0, s2), n1 = fmaxf(s1, s3);
#pragma unroll
                for (int o = 4; o < 32; o <<= 1) {
                    n0 = fmaxf(n0, __shfl_xor_sync(0xffffffffu, n0, o));
                    n1 = fmaxf(n1, __shfl_xor_sync(0xffffffffu, n1, o));
                }
                n0 = fmaxf(n0, m0); n1 = fmaxf(n1, m1);
                const float a0 = ex2((m0 - n0) * SC), a1 = ex2((m1 - n1) * SC);
                m0 = n0; m1 = n1; l0 *= a0; l1 *= a1;
#pragma unroll
                for (int m = 0; m < 8; m++) { oacc[m][0] *= a0; oacc[m][1] *= a1; oacc[m][2] *= a0; oacc[m][3] *= a1; }
            }
            const float mc0 = m0 * SC, mc1 = m1 * SC;
            const float p0 = ex2(fmaf(s0, SC, -mc0)), p1 = ex2(fmaf(s1, SC, -mc1));
            const float p2 = ex2(fmaf(s2, SC, -mc0)), p3 = ex2(fmaf(s3, SC, -mc1));
            l0 += p0 + p2; l1 += p1 + p3;
            const uint32_t pb0 = movmat(pack_bf16(p0, p1)), pb1 = movmat(pack_bf16(p2, p3));
            const uint32_t vt = sb + (slot + 1) * SLOT + offV;
            mbar_wait(bars + 8 * (BAR_FULL + slot + 1), use & 1);
#pragma unroll
            for (int mt = 0; mt < 8; mt++) {
                uint32_t a[4];
                ldsm4t(a, vt + (mt >> 2) * 8192 + (xV ^ ((mt & 3) << 5)));
                mma16816(oacc[mt], a, pb0, pb1);
            }
            __syncwarp();
            if (lane == 0) mbar_arrive(bars + 8 * (BAR_EMPTY + slot + 1));
            tp += 4;
            if (tp < PH2 + 4) { slot += 4; if (slot >= NSLOT) { slot -= NSLOT; use++; } }
            else use++;
        }
    }
    if (tid == 0) STAMP(6);
    if (tid == 128) STAMP(26);

    {
#pragma unroll
        for (int o = 4; o < 32; o <<= 1) { l0 += __shfl_xor_sync(0xffffffffu, l0, o); l1 += __shfl_xor_sync(0xffffffffu, l1, o); }
        const uint32_t ro = red + warp * 1024 + g * 8;
#pragma unroll
        for (int mt = 0; mt < 8; mt++) {
            if (t == (mt >> 1)) {
                sts64f(ro + mt * 128, oacc[mt][0], oacc[mt][1]);
                sts64f(ro + mt * 128 + 64, oacc[mt][2], oacc[mt][3]);
            }
        }
        if (lane == 0) sts128f(red + 8192 + warp * 16, m0, m1, l0, l1);
        u64* po = &scr->o[grp][mem][tid & 127];
        uint32_t rv = red + (tid & 63) * 16;
        PIN64(po); PIN32(rv);
        cbar();
        if (tid < 128) {
            const bool h = tid >= 64;
            float mw[8], lw[8], v0[8], v1[8];
#pragma unroll
            for (int w = 0; w < 8; w++) {
                const float4 a = lds128f(red + 8192 + w * 16), v = lds128f(rv + w * 1024);
                mw[w] = h ? a.y : a.x; lw[w] = h ? a.w : a.z;
                v0[w] = h ? v.y : v.x; v1[w] = h ? v.w : v.z;
            }
            const float M = fmaxf(fmaxf(fmaxf(mw[0], mw[1]), fmaxf(mw[2], mw[3])), fmaxf(fmaxf(mw[4], mw[5]), fmaxf(mw[6], mw[7])));
            float L = 0.f, o0 = 0.f, o1 = 0.f;
#pragma unroll
            for (int w = 0; w < 8; w++) {
                const float f = ex2((mw[w] - M) * SC);
                L = fmaf(f, lw[w], L); o0 = fmaf(f, v0[w], o0); o1 = fmaf(f, v1[w], o1);
            }
            const float inv = __fdividef(1.f, L);
            if (live) ll_st(po, pack_bf16(o0 * inv, o1 * inv), tag);
        }
    }
    if (tid == 0) STAMP(7);
    const int rl = (lane & 7) + ((lane >> 4) << 3);
    const uint32_t a72 = sb + rl * 144 + (2 * warp + ((lane >> 3) & 1)) * 16;
    u64 *pw0, *pw1;
    {
        const int c0 = min(16 * warp + g, 71), c1 = min(16 * warp + g + 8, 71);
        u64* pb = &scr->p1[mem][4 * t][grp][0];
        pw0 = pb + (c0 >= 36 ? 576 + c0 - 36 : c0);
        pw1 = pb + (c1 >= 36 ? 576 + c1 - 36 : c1);
    }
    const bool hi_ok = warp < 4;
    {
        uint32_t wa[16][4];
        if (live) { mbar_wait(bars + 8 * (BAR_T + 0), 0); mbar_wait(bars + 8 * (BAR_T + 1), 0); }
        gemv72_load<16>(wa, a72 + T_WO);
        if (tid == 0) STAMP(18);
        const u64* po = &scr->o[grp][warp][lane];
        uint32_t dst = actb + warp * ACTB_O_PITCH + lane * 4;
        uint32_t baddr = actb + (lane & 7) * ACTB_O_PITCH + (lane >> 3) * 16;
        PIN64(pw0); PIN64(pw1); PIN32(dst); PIN32(baddr);
        uint32_t ov[4] = {0u, 0u, 0u, 0u};
        if (live) ll_poll<4, 32>(po, tag, ov);
        if (tid == 0) STAMP(53);
        if (tid == 128) STAMP(54);
        if (tid == 224) STAMP(55);
#pragma unroll
        for (int k = 0; k < 4; k++) sts32(dst + 128 * k, ov[k]);
        cbar();
        if (tid == 0) STAMP(8);
        if (warp < 5) gemv72_run<16>(wa, baddr, pw0, pw1, hi_ok, tag, live, sb, 52);
        if (tid == 0) STAMP(21);
    }
    uint32_t x1_r = 0;
    const u64* pr = &scr->p1[mem][grp][2 * warp][lane < 18 ? 2 * lane : 0];
    {
        u64* px = &scr->x1[rb][12 * mem + 6 * (grp & 1) + (lane < 6 ? lane : 0)][0];
        int src = lane < 6 ? 3 * lane : 0;
        PIN64(px); PIN32(src);
        float a0 = 0.f, a1 = 0.f;
        reduce16(pr, red, warp, lane, tag, live, a0, a1);
        if (warp == 7) {
            x1_r = pack_bf16(fmaf(bf_lo(ga_r), a0, bf_lo(x_r)), fmaf(bf_hi(ga_r), a1, bf_hi(x_r)));
            const uint32_t w0 = __shfl_sync(0xffffffffu, x1_r, src), w1 = __shfl_sync(0xffffffffu, x1_r, src + 1),
                           w2 = __shfl_sync(0xffffffffu, x1_r, src + 2);
            if (live && lane < 6) ll_st128(px, w0, w1, w2, tag);
            if (lane == 0) STAMP(9);
        }
    }
    {
        const int mat = warp >> 2, kg = warp & 3;
        if (live) {
#pragma unroll 1
            for (int p = 0; p < 3; p++) mbar_wait(bars + 8 * (BAR_T + 2 + 3 * mat + p), 0);
        }
        if (tid == 0) STAMP(19);
        const uint32_t aaddr = sb + (mat ? T_WU : T_WG) + (144 * kg + rl) * 80 + ((lane >> 3) & 1) * 16;
        uint32_t wa[9][3][4];
#pragma unroll
        for (int i = 0; i < 6; i++)
#pragma unroll
            for (int m = 0; m < 3; m++) ldsm4t(wa[i][m], aaddr + i * 16 * 80 + m * 32);

        const u64* xp = &scr->x1[warp][lane][0];
        uint32_t adst = act_row + 12 * lane;
        uint32_t baddr = act + (lane & 7) * ACT_PITCH + (lane >> 3) * 16 + 288 * kg;
        PIN32(adst); PIN32(baddr);
        uint32_t xv[9] = {0u, 0u, 0u, 0u, 0u, 0u, 0u, 0u, 0u};
        if (live) {
            int it = 0;
            uint32_t bad;
            do {
                bad = 0;
#pragma unroll
                for (int k = 0; k < 3; k++) {
                    uint32_t tg;
                    ll_ld128(xp + 64 * k, xv[3 * k], xv[3 * k + 1], xv[3 * k + 2], tg);
                    bad |= tg ^ tag;
                }
            } while (!poll_done(bad, it));
        }
        if (tid == 0) STAMP(23);
        float mean, den;
        ln_stats(xv, mean, den);
        const uint32_t m2 = pack_bf16(mean, mean);
        const float rinv = __frcp_rn(den);
#pragma unroll
        for (int k = 0; k < 9; k++) sts32(adst + 384 * (k / 3) + 4 * (k % 3), ln_mod2(xv[k], m2, rinv, cbv[k], sbv[k]));
#pragma unroll
        for (int i = 6; i < 9; i++)
#pragma unroll
            for (int m = 0; m < 3; m++) ldsm4t(wa[i][m], aaddr + i * 16 * 80 + m * 32);
        uint32_t rdst = red + warp * 1536 + g * 32 + t * 8;
        uint32_t rsrc = red + (((36 * cta) & 7) + 2 * (tid >> 3)) * 32 + (tid & 7) * 4;
        u64* ph = &scr->hh[grp][18 * mem][0] + (tid < 144 ? tid : 0);
        PIN32(rdst); PIN32(rsrc); PIN64(ph);
        cbar();
        if (tid == 0) STAMP(10);
        float c[2][3][4];
#pragma unroll
        for (int m = 0; m < 3; m++)
#pragma unroll
            for (int j = 0; j < 4; j++) c[0][m][j] = c[1][m][j] = 0.f;
#pragma unroll
        for (int i = 0; i < 9; i += 2) {
            uint32_t b[4];
            ldsm4(b, baddr + i * 32);
#pragma unroll
            for (int m = 0; m < 3; m++) {
                mma16816(c[0][m], wa[i][m], b[0], b[1]);
                if (i + 1 < 9) mma16816(c[1][m], wa[i + 1][m], b[2], b[3]);
            }
        }
#pragma unroll
        for (int m = 0; m < 3; m++) {
            sts64f(rdst + m * 512, c[0][m][0] + c[1][m][0], c[0][m][1] + c[1][m][1]);
            sts64f(rdst + m * 512 + 256, c[0][m][2] + c[1][m][2], c[0][m][3] + c[1][m][3]);
        }
        if (tid == 0) STAMP(24);
        cbar();
        if (tid < 144) {
            float r[2];
#pragma unroll
            for (int e = 0; e < 2; e++) {
                const uint32_t a = rsrc + 32 * e;
                const float gg = (ldsf(a) + ldsf(a + 1536)) + (ldsf(a + 3072) + ldsf(a + 4608));
                const float uu = (ldsf(a + 6144) + ldsf(a + 7680)) + (ldsf(a + 9216) + ldsf(a + 10752));
                r[e] = gelu_f(gg) * uu;
            }
            if (live) ll_st(ph, pack_bf16(r[0], r[1]), tag);
        }
        if (live && cta == 0 && tid == 255) {
            asm volatile("st.relaxed.gpu.global.u32 [%0], %1;" ::"l"(&scr->epoch), "r"(tag) : "memory");
            asm volatile("st.relaxed.gpu.global.u32 [%0], %1;" ::"l"(&scr->prog), "r"(0u) : "memory");
        }
    }
    if (tid == 0) STAMP(11);
    {
        uint32_t wa[18][4];
        if (live) {
#pragma unroll 1
            for (int p = 0; p < 3; p++) mbar_wait(bars + 8 * (BAR_T + 8 + p), 0);
        }
        gemv72_load<18>(wa, a72 + T_WD);
        if (tid == 0) STAMP(20);
        const u64* hp = &scr->hh[grp][0][0] + tid;
        const u64* hl = &scr->hh[grp][128][0] + (tid & 127);
        uint32_t dst = actb + (tid & 7) * ACTB_H_PITCH + (tid >> 3) * 4;
        uint32_t dl = actb + (tid & 7) * ACTB_H_PITCH + (128 + ((tid & 127) >> 3)) * 4;
        uint32_t baddr = actb + (lane & 7) * ACTB_H_PITCH + (lane >> 3) * 16;
        u64 *q0 = pw0 + P2_MINUS_P1, *q1 = pw1 + P2_MINUS_P1;
        PIN32(dst); PIN32(dl); PIN32(baddr); PIN64(q0); PIN64(q1);
        uint32_t hv[5] = {0u, 0u, 0u, 0u, 0u};
        if (live) {
            int it = 0;
            uint32_t bad;
            do {
                bad = 0;
#pragma unroll
                for (int k = 0; k < 5; k++) { uint32_t tg; ll_ld(k < 4 ? hp + 256 * k : hl, hv[k], tg); bad |= tg ^ tag; }
            } while (!poll_done(bad, it));
        }
#pragma unroll
        for (int k = 0; k < 4; k++) sts32(dst + 128 * k, hv[k]);
        sts32(dl, hv[4]);
        cbar();
        if (tid == 0) STAMP(12);
        if (warp < 5) gemv72_run<18>(wa, baddr, q0, q1, hi_ok, tag, live);
        if (tid == 0) STAMP(22);
    }
    {
        uint32_t* po = reinterpret_cast<uint32_t*>(prm.out + rb * DM) + rpair;
        PIN64(po);
        float a0 = 0.f, a1 = 0.f;
        reduce16(pr + P2_MINUS_P1, red, warp, lane, tag, live, a0, a1);
        if (warp == 7) {
            if (live && lane < 18) *po = pack_bf16(fmaf(bf_lo(gb_r), a0, bf_lo(x1_r)), fmaf(bf_hi(gb_r), a1, bf_hi(x1_r)));
            if (lane == 0) STAMP(13);
        }
    }
    }
}

typedef CUresult (*EncodeFn)(CUtensorMap*, CUtensorMapDataType, cuuint32_t, void*, const cuuint64_t*, const cuuint64_t*,
                             const cuuint32_t*, const cuuint32_t*, CUtensorMapInterleave, CUtensorMapSwizzle,
                             CUtensorMapL2promotion, CUtensorMapFloatOOBfill);

void make_map2d(EncodeFn enc, CUtensorMap* m, const void* ptr, uint64_t cols, uint64_t rows, uint32_t bc, uint32_t br,
                CUtensorMapSwizzle sw, CUtensorMapL2promotion pr) {
    cuuint64_t dims[2] = {cols, rows};
    cuuint64_t strides[1] = {cols * 2};
    cuuint32_t box[2] = {bc, br};
    cuuint32_t es[2] = {1, 1};
    enc(m, CU_TENSOR_MAP_DATA_TYPE_BFLOAT16, 2, const_cast<void*>(ptr), dims, strides, box, es,
        CU_TENSOR_MAP_INTERLEAVE_NONE, sw, pr, CU_TENSOR_MAP_FLOAT_OOB_FILL_NONE);
}
void make_map_kv(EncodeFn enc, CUtensorMap* m, const void* ptr) {
    cuuint64_t dims[3] = {64, (cuuint64_t)NB * 16 * SK, 2};
    cuuint64_t strides[2] = {256, 128};
    cuuint32_t box[3] = {64, 64, 2};
    cuuint32_t es[3] = {1, 1, 1};
    enc(m, CU_TENSOR_MAP_DATA_TYPE_BFLOAT16, 3, const_cast<void*>(ptr), dims, strides, box, es,
        CU_TENSOR_MAP_INTERLEAVE_NONE, CU_TENSOR_MAP_SWIZZLE_128B, CU_TENSOR_MAP_L2_PROMOTION_L2_256B,
        CU_TENSOR_MAP_FLOAT_OOB_FILL_NONE);
}

}

extern "C" void kernel_launch(void* const* d_in, const int* in_sizes, int n_in, void* d_out, int out_size) {
    (void)in_sizes; (void)n_in; (void)out_size;
    static EncodeFn enc = nullptr;
    static Scratch* scr = nullptr;
    if (!enc) {
        void* fn = nullptr;
        cudaDriverEntryPointQueryResult qr;
        cudaGetDriverEntryPoint("cuTensorMapEncodeTiled", &fn, cudaEnableDefault, &qr);
        enc = (EncodeFn)fn;
        cudaGetSymbolAddress((void**)&scr, g_scr);
        cudaFuncSetAttribute(adaln_gqa_geglu_decode_kernel, cudaFuncAttributeMaxDynamicSharedMemorySize, SMEM_BYTES);
    }
    CUtensorMap tmK, tmV, tmMod, tmWq, tmWo, tmWg, tmWu, tmWd;
    make_map_kv(enc, &tmK, d_in[1]);
    make_map_kv(enc, &tmV, d_in[2]);
    make_map2d(enc, &tmMod, d_in[10], 6 * DM, DM, 32, 192, CU_TENSOR_MAP_SWIZZLE_64B, CU_TENSOR_MAP_L2_PROMOTION_L2_128B);
    make_map2d(enc, &tmWq, d_in[3], 4096, DM, 32, 192, CU_TENSOR_MAP_SWIZZLE_64B, CU_TENSOR_MAP_L2_PROMOTION_L2_128B);
    make_map2d(enc, &tmWo, d_in[4], DM, 4096, 72, 128, CU_TENSOR_MAP_SWIZZLE_NONE, CU_TENSOR_MAP_L2_PROMOTION_L2_128B);
    make_map2d(enc, &tmWg, d_in[6], DF, DM, 40, 192, CU_TENSOR_MAP_SWIZZLE_NONE, CU_TENSOR_MAP_L2_PROMOTION_L2_128B);
    make_map2d(enc, &tmWu, d_in[7], DF, DM, 40, 192, CU_TENSOR_MAP_SWIZZLE_NONE, CU_TENSOR_MAP_L2_PROMOTION_L2_128B);
    make_map2d(enc, &tmWd, d_in[8], DM, DF, 72, 96, CU_TENSOR_MAP_SWIZZLE_NONE, CU_TENSOR_MAP_L2_PROMOTION_L2_128B);
    Params prm;
    prm.x = (const __nv_bfloat16*)d_in[0];
    prm.c = (const __nv_bfloat16*)d_in[9];
    prm.wmod = (const __nv_bfloat16*)d_in[10];
    prm.k = (const __nv_bfloat16*)d_in[1];
    prm.v = (const __nv_bfloat16*)d_in[2];
    prm.out = (__nv_bfloat16*)d_out;
    prm.scr = scr;
    adaln_gqa_geglu_decode_kernel<<<NCTA, NTHREADS, SMEM_BYTES, cudaStreamPerThread>>>(prm, tmK, tmV, tmMod, tmWq, tmWo, tmWg, tmWu, tmWd);
}
```

```cpp
#include <cuda_runtime.h>
#include <cuda_bf16.h>
#include <cuda.h>
#include <stdint.h>
#include <stddef.h>

namespace {

typedef unsigned long long u64;

constexpr int NB = 8;
constexpr int DM = 576;
constexpr int SK = 8192;
constexpr int DF = 4608;
constexpr int NCTA = 128;
constexpr int NXTRA = 4;
constexpr int NTHREADS = 288;

constexpr int NSLOT = 12;
constexpr int SLOT = 16384;
constexpr int RING = NSLOT * SLOT;
constexpr int P_REG = DM * 64;
constexpr int P_A = 3 * SLOT;
constexpr int P_B = P_A + P_REG;
constexpr int T_WO = 0;
constexpr int T_WG = T_WO + 256 * 144;
constexpr int T_WU = T_WG + DM * 80;
constexpr int T_WD = T_WU + DM * 80;
constexpr int T_END = T_WD + 288 * 144;
static_assert(T_END <= RING, "tail overlay");
static_assert(P_B + P_REG <= 8 * SLOT, "prologue overlay");
constexpr int ACT_PITCH = 1168;
constexpr int OFF_ACT = RING;
constexpr int OFF_RED = OFF_ACT + NB * ACT_PITCH;
constexpr int RED_BYTES = 12288 + 256;
constexpr int ACTB_O_PITCH = 528;
constexpr int ACTB_H_PITCH = 592;
constexpr int OFF_ACTB = OFF_RED + RED_BYTES;
constexpr int OFF_STAT = OFF_ACTB + NB * ACTB_H_PITCH;
constexpr int OFF_BAR = OFF_STAT + 128;
constexpr int BAR_FULL = 0, BAR_EMPTY = NSLOT, BAR_P = 2 * NSLOT, BAR_T = BAR_P + 6;
constexpr int NT_PIECES = 11;
constexpr int NBARS = BAR_T + NT_PIECES;
constexpr int OFF_Q = OFF_BAR + NBARS * 8;
constexpr int OFF_STAMP = OFF_Q + 16 * 8;
constexpr int SMEM_USED = OFF_STAMP + 96 * 8;
constexpr int SMEM_BYTES = SMEM_USED + 1024;
static_assert(SMEM_BYTES <= 232448, "smem");

constexpr int NTILES = 256;
constexpr int TILE0 = 8;
constexpr int TILE_END = TILE0 + NTILES;
constexpr int LAST_USE = (TILE_END - 1) / NSLOT;
static_assert(TILE_END % NSLOT == 0, "last round must end with the last slot");

#define PACE_D0 4
#define PACE_GAIN 6
#define PACE_BIAS 0
#define PACE_DMIN 1
#define PACE_DMAX 8
#define PACE_DSTART 3
#define MID_KB 64
#define START_TILES 2
#define WIN_T 40000

constexpr int SPIN_LIMIT = 1 << 21;

struct Scratch {
    u64 h0[NB][128][2];
    u64 mod[NB][1152];
    u64 q[16][NB][128];
    u64 o[16][NB][128];
    u64 p1[8][16][16][36];
    u64 x1[NB][96][2];
    u64 hh[16][144][NB];
    u64 p2[8][16][16][36];
    unsigned int epoch, pad0[31];
    unsigned int prog, pad1[31];
};
__device__ __align__(1024) Scratch g_scr;
constexpr int P2_MINUS_P1 = (int)((offsetof(Scratch, p2) - offsetof(Scratch, p1)) / 8);

#define PIN32(x) asm volatile("" : "+r"(x))
#define PIN64(x) asm volatile("" : "+l"(x))

__device__ __forceinline__ uint32_t smem_u32(const void* p) { return (uint32_t)__cvta_generic_to_shared(p); }
__device__ __forceinline__ void sts32(uint32_t a, uint32_t v) { asm volatile("st.shared.b32 [%0], %1;" ::"r"(a), "r"(v) : "memory"); }
__device__ __forceinline__ void sts64f(uint32_t a, float x, float y) { asm volatile("st.shared.v2.f32 [%0], {%1, %2};" ::"r"(a), "f"(x), "f"(y) : "memory"); }
__device__ __forceinline__ void sts128f(uint32_t a, float x, float y, float z, float w) {
    asm volatile("st.shared.v4.f32 [%0], {%1, %2, %3, %4};" ::"r"(a), "f"(x), "f"(y), "f"(z), "f"(w) : "memory");
}
__device__ __forceinline__ uint32_t lds32(uint32_t a) { uint32_t v; asm volatile("ld.shared.b32 %0, [%1];" : "=r"(v) : "r"(a)); return v; }
__device__ __forceinline__ float ldsf(uint32_t a) { float v; asm volatile("ld.shared.f32 %0, [%1];" : "=f"(v) : "r"(a)); return v; }
__device__ __forceinline__ float4 lds128f(uint32_t a) {
    float4 v;
    asm volatile("ld.shared.v4.f32 {%0, %1, %2, %3}, [%4];" : "=f"(v.x), "=f"(v.y), "=f"(v.z), "=f"(v.w) : "r"(a));
    return v;
}

#define STAMP(i) do {} while (0)

__device__ __forceinline__ void mbar_init(uint32_t bar, uint32_t cnt) {
    asm volatile("mbarrier.init.shared::cta.b64 [%0], %1;" ::"r"(bar), "r"(cnt) : "memory");
}
__device__ __forceinline__ void mbar_expect_tx(uint32_t bar, uint32_t bytes) {
    asm volatile("mbarrier.arrive.expect_tx.shared::cta.b64 _, [%0], %1;" ::"r"(bar), "r"(bytes) : "memory");
}
__device__ __forceinline__ void mbar_arrive(uint32_t bar) {
    asm volatile("mbarrier.arrive.shared::cta.b64 _, [%0];" ::"r"(bar) : "memory");
}
__device__ __forceinline__ void mbar_arrive_n(uint32_t bar, uint32_t n) {
    asm volatile("mbarrier.arrive.shared::cta.b64 _, [%0], %1;" ::"r"(bar), "r"(n) : "memory");
}
__device__ __forceinline__ void mbar_wait(uint32_t bar, uint32_t parity) {
    asm volatile(
        "{\n.reg .pred p;\n.reg .u32 n;\nmov.u32 n, 0;\n"
        "W: mbarrier.try_wait.parity.shared::cta.b64 p, [%0], %1;\n"
        "@p bra D;\nadd.u32 n, n, 1;\nsetp.lt.u32 p, n, %2;\n@p bra W;\ntrap;\nD:\n}"
        ::"r"(bar), "r"(parity), "n"(SPIN_LIMIT) : "memory");
}
__device__ __forceinline__ void cbar() { asm volatile("bar.sync 1, 256;" ::: "memory"); }

__device__ __forceinline__ void tma2d(uint32_t dst, const CUtensorMap* tm, int c0, int c1, uint32_t bar) {
    asm volatile("cp.async.bulk.tensor.2d.shared::cluster.global.mbarrier::complete_tx::bytes [%0], [%1, {%3, %4}], [%2];"
                 ::"r"(dst), "l"(tm), "r"(bar), "r"(c0), "r"(c1) : "memory");
}
__device__ __forceinline__ void tma3d_hint(uint32_t dst, const CUtensorMap* tm, int c0, int c1, int c2, uint32_t bar, uint64_t pol) {
    asm volatile("cp.async.bulk.tensor.3d.shared::cluster.global.mbarrier::complete_tx::bytes.L2::cache_hint [%0], [%1, {%3, %4, %5}], [%2], %6;"
                 ::"r"(dst), "l"(tm), "r"(bar), "r"(c0), "r"(c1), "r"(c2), "l"(pol) : "memory");
}
__device__ __forceinline__ void ldsm4(uint32_t (&r)[4], uint32_t a) {
    asm volatile("ldmatrix.sync.aligned.m8n8.x4.shared.b16 {%0,%1,%2,%3}, [%4];"
                 : "=r"(r[0]), "=r"(r[1]), "=r"(r[2]), "=r"(r[3]) : "r"(a));
}
__device__ __forceinline__ void ldsm4t(uint32_t (&r)[4], uint32_t a) {
    asm volatile("ldmatrix.sync.aligned.m8n8.x4.trans.shared.b16 {%0,%1,%2,%3}, [%4];"
                 : "=r"(r[0]), "=r"(r[1]), "=r"(r[2]), "=r"(r[3]) : "r"(a));
}
__device__ __forceinline__ void ldsm2(uint32_t& r0, uint32_t& r1, uint32_t a) {
    asm volatile("ldmatrix.sync.aligned.m8n8.x2.shared.b16 {%0,%1}, [%2];" : "=r"(r0), "=r"(r1) : "r"(a));
}
__device__ __forceinline__ void mma16816(float (&c)[4], const uint32_t (&a)[4], uint32_t b0, uint32_t b1) {
    asm volatile("mma.sync.aligned.m16n8k16.row.col.f32.bf16.bf16.f32 {%0,%1,%2,%3}, {%4,%5,%6,%7}, {%8,%9}, {%0,%1,%2,%3};"
                 : "+f"(c[0]), "+f"(c[1]), "+f"(c[2]), "+f"(c[3])
                 : "r"(a[0]), "r"(a[1]), "r"(a[2]), "r"(a[3]), "r"(b0), "r"(b1));
}
__device__ __forceinline__ uint32_t movmat(uint32_t a) {
    uint32_t d;
    asm volatile("movmatrix.sync.aligned.m8n8.trans.b16 %0, %1;" : "=r"(d) : "r"(a));
    return d;
}
__device__ __forceinline__ float ex2(float x) {
    float y;
    asm("ex2.approx.ftz.f32 %0, %1;" : "=f"(y) : "f"(x));
    return y;
}
__device__ __forceinline__ uint32_t pack_bf16(float lo, float hi) {
    __nv_bfloat162 v = __floats2bfloat162_rn(lo, hi);
    return *reinterpret_cast<uint32_t*>(&v);
}
__device__ __forceinline__ float bf_lo(uint32_t v) { return __uint_as_float(v << 16); }
__device__ __forceinline__ float bf_hi(uint32_t v) { return __uint_as_float(v & 0xffff0000u); }
__device__ __forceinline__ float rbf(float x) { return __bfloat162float(__float2bfloat16_rn(x)); }

__device__ __forceinline__ void ll_st(u64* p, uint32_t data, uint32_t tag) {
    asm volatile("{\n.reg .b64 v;\nmov.b64 v, {%1, %2};\nst.relaxed.gpu.global.b64 [%0], v;\n}" ::"l"(p), "r"(data), "r"(tag) : "memory");
}
__device__ __forceinline__ void ll_ld(const u64* p, uint32_t& data, uint32_t& tg) {
    asm volatile("{\n.reg .b64 v;\nld.relaxed.gpu.global.b64 v, [%2];\nmov.b64 {%0, %1}, v;\n}" : "=r"(data), "=r"(tg) : "l"(p) : "memory");
}
__device__ __forceinline__ void ll_ld2(const u64* p, uint32_t& d0, uint32_t& t0, uint32_t& d1, uint32_t& t1) {
    asm volatile("{\n.reg .b64 a, b;\nld.relaxed.gpu.global.v2.b64 {a, b}, [%4];\nmov.b64 {%0, %1}, a;\nmov.b64 {%2, %3}, b;\n}"
                 : "=r"(d0), "=r"(t0), "=r"(d1), "=r"(t1) : "l"(p) : "memory");
}
__device__ __forceinline__ void ll_st128(u64* p, uint32_t w0, uint32_t w1, uint32_t w2, uint32_t tag) {
    asm volatile("{\n.reg .b128 r;\n.reg .b64 lo, hi;\nmov.b64 lo, {%1, %2};\nmov.b64 hi, {%3, %4};\nmov.b128 r, {lo, hi};\n"
                 "st.relaxed.gpu.global.b128 [%0], r;\n}" ::"l"(p), "r"(w0), "r"(w1), "r"(w2), "r"(tag) : "memory");
}
__device__ __forceinline__ void ll_ld128(const u64* p, uint32_t& w0, uint32_t& w1, uint32_t& w2, uint32_t& tg) {
    asm volatile("{\n.reg .b128 r;\n.reg .b64 lo, hi;\nld.relaxed.gpu.global.b128 r, [%4];\nmov.b128 {lo, hi}, r;\n"
                 "mov.b64 {%0, %1}, lo;\nmov.b64 {%2, %3}, hi;\n}" : "=r"(w0), "=r"(w1), "=r"(w2), "=r"(tg) : "l"(p) : "memory");
}
__device__ __forceinline__ bool poll_done(uint32_t bad, int& it) {
    if (!__any_sync(0xffffffffu, bad != 0)) return true;
    if (++it > SPIN_LIMIT) __trap();
    return false;
}
template <int N, int STRIDE>
__device__ __forceinline__ void ll_poll(const u64* p, uint32_t tag, uint32_t (&out)[N]) {
    int it = 0;
    uint32_t bad;
    do {
        bad = 0;
#pragma unroll
        for (int i = 0; i < N; i++) { uint32_t tg; ll_ld(p + i * STRIDE, out[i], tg); bad |= tg ^ tag; }
    } while (!poll_done(bad, it));
}
__device__ __forceinline__ void reduce16(const u64* p, uint32_t buf, int warp, int lane, uint32_t tag, float& s0, float& s1) {
    uint32_t a0, a1, b0, b1;
    {
        int it = 0;
        uint32_t bad;
        do {
            uint32_t t0, t1, t2, t3;
            ll_ld2(p, a0, t0, a1, t1);
            ll_ld2(p + 36, b0, t2, b1, t3);
            bad = ((t0 ^ tag) | (t1 ^ tag)) | ((t2 ^ tag) | (t3 ^ tag));
        } while (!poll_done(bad, it));
    }
    if (lane < 18) sts64f(buf + (warp * 18 + lane) * 8, __uint_as_float(a0) + __uint_as_float(b0), __uint_as_float(a1) + __uint_as_float(b1));
    if (warp != 7) {
        asm volatile("bar.arrive 3, 256;" ::: "memory");
    } else {
        asm volatile("bar.sync 3, 256;" ::: "memory");
        float x[8], y[8];
        const uint32_t q = buf + (lane < 18 ? lane : 0) * 8;
#pragma unroll
        for (int w = 0; w < 8; w++) asm volatile("ld.shared.v2.f32 {%0, %1}, [%2];" : "=f"(x[w]), "=f"(y[w]) : "r"(q + w * 144));
        s0 = ((x[0] + x[1]) + (x[2] + x[3])) + ((x[4] + x[5]) + (x[6] + x[7]));
        s1 = ((y[0] + y[1]) + (y[2] + y[3])) + ((y[4] + y[5]) + (y[6] + y[7]));
    }
}

template <bool FAST>
__device__ __forceinline__ void ln_stats(const uint32_t (&v)[9], float& mean, float& den) {
    const float k = __shfl_sync(0xffffffffu, bf_lo(v[0]), 0);
    float s = 0.f, q = 0.f;
#pragma unroll
    for (int i = 0; i < 9; i++) {
        const float a = bf_lo(v[i]) - k, b = bf_hi(v[i]) - k;
        s += a + b;
        q = fmaf(a, a, fmaf(b, b, q));
    }
#pragma unroll
    for (int o = 16; o > 0; o >>= 1) { s += __shfl_xor_sync(0xffffffffu, s, o); q += __shfl_xor_sync(0xffffffffu, q, o); }
    const float md = s * (1.0f / DM);
    mean = rbf(k + md);
    const float ve = rbf(rbf(fmaxf(q * (1.0f / DM) - md * md, 0.f)) + 1e-5f);
    float r;
    if (FAST) asm("sqrt.approx.f32 %0, %1;" : "=f"(r) : "f"(ve)); else r = __fsqrt_rn(ve);
    den = rbf(r);
}
__device__ __forceinline__ uint32_t bf2_add(uint32_t a, uint32_t b) {
    uint32_t d; asm("add.rn.bf16x2 %0, %1, %2;" : "=r"(d) : "r"(a), "r"(b)); return d;
}
__device__ __forceinline__ uint32_t bf2_sub(uint32_t a, uint32_t b) {
    uint32_t d; asm("sub.rn.bf16x2 %0, %1, %2;" : "=r"(d) : "r"(a), "r"(b)); return d;
}
__device__ __forceinline__ uint32_t bf2_mul(uint32_t a, uint32_t b) {
    uint32_t d; asm("mul.rn.bf16x2 %0, %1, %2;" : "=r"(d) : "r"(a), "r"(b)); return d;
}
__device__ __forceinline__ uint32_t ln_mod2(uint32_t x, uint32_t m2, float rinv, uint32_t c1, uint32_t sh) {
    const uint32_t d = bf2_sub(x, m2);
    const uint32_t n = pack_bf16(bf_lo(d) * rinv, bf_hi(d) * rinv);
    return bf2_add(bf2_mul(n, c1), sh);
}
constexpr uint32_t BF2_ONE = 0x3f803f80u;
__device__ __forceinline__ float silu_f(float a) { return __fdividef(a, 1.f + __expf(-a)); }
__device__ __forceinline__ float gelu_f(float g) {
    const float z2 = 1.5957691216057308f * fmaf(0.044715f * g * g, g, g);
    return __fdividef(g, 1.f + __expf(-z2));
}

template <int KSTEPS>
__device__ __forceinline__ void gemv72_load(uint32_t (&a)[KSTEPS][4], uint32_t aaddr) {
#pragma unroll
    for (int i = 0; i < KSTEPS; i++) ldsm4t(a[i], aaddr + i * 16 * 144);
}
template <int KSTEPS>
__device__ __forceinline__ void gemv72_run(const uint32_t (&a)[KSTEPS][4], uint32_t baddr, u64* p0, u64* p1, bool hi_ok, uint32_t tag) {
    float c[4][4];
#pragma unroll
    for (int j = 0; j < 4; j++) c[j][0] = c[j][1] = c[j][2] = c[j][3] = 0.f;
#pragma unroll
    for (int i = 0; i < KSTEPS; i += 2) {
        uint32_t b[4];
        ldsm4(b, baddr + i * 32);
        mma16816(c[i & 3], a[i], b[0], b[1]);
        mma16816(c[(i + 1) & 3], a[i + 1], b[2], b[3]);
    }
    const float r0 = (c[0][0] + c[1][0]) + (c[2][0] + c[3][0]), r1 = (c[0][1] + c[1][1]) + (c[2][1] + c[3][1]);
    const float r2 = (c[0][2] + c[1][2]) + (c[2][2] + c[3][2]), r3 = (c[0][3] + c[1][3]) + (c[2][3] + c[3][3]);
    ll_st(p0, __float_as_uint(r0), tag); ll_st(p0 + 2 * 576, __float_as_uint(r1), tag);
    if (hi_ok) { ll_st(p1, __float_as_uint(r2), tag); ll_st(p1 + 2 * 576, __float_as_uint(r3), tag); }
}

struct Params {
    const __nv_bfloat16* x;
    const __nv_bfloat16* c;
    const __nv_bfloat16* wmod;
    __nv_bfloat16* out;
    Scratch* scr;
};

__global__ void __launch_bounds__(NTHREADS, 1)
adaln_gqa_geglu_decode_kernel(const Params prm,
                              const __grid_constant__ CUtensorMap tmK, const __grid_constant__ CUtensorMap tmV,
                              const __grid_constant__ CUtensorMap tmMod, const __grid_constant__ CUtensorMap tmWq,
                              const __grid_constant__ CUtensorMap tmWo, const __grid_constant__ CUtensorMap tmWg,
                              const __grid_constant__ CUtensorMap tmWu, const __grid_constant__ CUtensorMap tmWd) {
    extern __shared__ unsigned char smem_raw[];
    uint32_t sb = (smem_u32(smem_raw) + 1023u) & ~1023u;
    int tid = threadIdx.x, cta = blockIdx.x;
    Scratch* scr = prm.scr;
    PIN32(sb); PIN32(tid); PIN32(cta); PIN64(scr);
    const uint32_t bars = sb + OFF_BAR;
    const int warp = tid >> 5, lane = tid & 31;
    const int grp = cta >> 3, mem = cta & 7;
    const bool extra = cta >= NCTA;

    if (warp == 8) {
        if (lane < 8) {
            const CUtensorMap* tm = lane == 0 ? &tmMod : lane == 1 ? &tmWq : lane == 2 ? &tmK : lane == 3 ? &tmV
                                  : lane == 4 ? &tmWo : lane == 5 ? &tmWg : lane == 6 ? &tmWu : &tmWd;
            asm volatile("prefetch.tensormap [%0];" ::"l"(tm) : "memory");
        }
        if (lane == 0) {
            STAMP(0);
        }
        if (lane == 0) {
#pragma unroll
            for (int s = 0; s < NBARS; s++) mbar_init(bars + 8 * s, (s >= BAR_EMPTY && s < BAR_P) ? 4 : 1);
#pragma unroll
            for (int s = 0; s < 8; s++) {
                mbar_arrive(bars + 8 * (BAR_FULL + s));
                if (s < 3 || (s >= 6 && cta >= 36)) mbar_arrive_n(bars + 8 * (BAR_EMPTY + s), 4);
            }
            asm volatile("fence.mbarrier_init.release.cluster;" ::: "memory");
        }
        __syncwarp();
        if (lane == 0) STAMP(41);
        asm volatile("bar.arrive 2, 288;" ::: "memory");
        if (lane == 0 && !extra) {
            uint64_t pol;
            asm volatile("createpolicy.fractional.L2::evict_first.b64 %0, 1.0;" : "=l"(pol));
            const uint32_t fifo = sb + OFF_Q;
            const int row0 = (mem * 16 + grp) * SK;
            const int boxcol = (36 * cta) & ~7;
            int head = 0, tail = 0, inflight = 0;
            int pi = 0, tp = TILE0, ti = 0, freed = 0, slot = TILE0, use = 0, win = PACE_DSTART, own_at = 0;
            unsigned gpend = 0;
#pragma unroll 1
            while (true) {
                uint32_t bar, par = 0;
                int bytes, window, kind;
                if (pi < 3) {
                    kind = 0; bar = bars + 8 * (BAR_P + (cta < 36 ? 3 : 0) + pi); bytes = 12288; window = 1 << 30;
                } else if (tp < TILE_END) {
                    kind = 1;
                    if (use > 0) mbar_wait(bars + 8 * (BAR_EMPTY + slot), (use - 1) & 1);
                    if (PACE_GAIN > 0 && (tp & 1) == 0) {
                        if (tp >= TILE0 + 12) {
                            const int sc = (own_at * NCTA - (int)gpend - PACE_BIAS) * PACE_GAIN;
                            const int adj = sc >= 0 ? (sc + 2 * NCTA) / (4 * NCTA) : -((-sc + 2 * NCTA) / (4 * NCTA));
                            win = min(max(PACE_D0 - adj, PACE_DMIN), PACE_DMAX);
                        }
                        asm volatile("red.relaxed.gpu.global.add.u32 [%0], 1;" ::"l"(&scr->prog) : "memory");
                        own_at = ((tp - TILE0) >> 1) + 1;
                        asm volatile("ld.relaxed.gpu.global.u32 %0, [%1];" : "=r"(gpend) : "l"(&scr->prog) : "memory");
                    } else if (PACE_GAIN == 0 && tp >= TILE0 + 12) win = PACE_D0;
                    bar = bars + 8 * (BAR_FULL + slot); par = use & 1; bytes = SLOT; window = tp < TILE0 + START_TILES ? (1 << 30) : win * SLOT;
                } else if (ti < NT_PIECES) {
                    kind = 2;
                    bytes = ti < 2 ? 18432 : ti < 8 ? 15360 : 13824;
                    const int end = ti < 2 ? 18432 * (ti + 1) : ti < 8 ? T_WG + 15360 * (ti - 1) : T_WD + 13824 * (ti - 7);
                    while (freed * SLOT < end) { mbar_wait(bars + 8 * (BAR_EMPTY + freed), LAST_USE & 1); freed++; }
                    bar = bars + 8 * (BAR_T + ti);
                    window = WIN_T;
                } else break;
                while (head != tail && inflight + bytes > window) {
                    const uint32_t e = lds32(fifo + 8 * (head & 15));
                    mbar_wait(e & ~1u, e & 1u);
                    inflight -= (int)lds32(fifo + 8 * (head & 15) + 4);
                    head++;
                }
                sts32(fifo + 8 * (tail & 15), bar | par); sts32(fifo + 8 * (tail & 15) + 4, bytes);
                tail++; inflight += bytes;
                mbar_expect_tx(bar, bytes);
                if (kind == 0) {
                    tma2d(sb + (cta < 36 ? P_B : P_A) + pi * 12288, &tmWq, 32 * cta, 192 * pi, bar);
                    pi++;
                } else if (kind == 1) {
                    tma3d_hint(sb + slot * SLOT, (tp & 1) ? &tmV : &tmK, 0, row0 + ((tp - TILE0) >> 1) * 64, 0, bar, pol);
                    if (++slot == NSLOT) { slot = 0; use++; }
                    tp++;
                } else {
                    const CUtensorMap* tm = ti < 2 ? &tmWo : ti < 5 ? &tmWg : ti < 8 ? &tmWu : &tmWd;
                    const int off = ti < 2 ? 18432 * ti : ti < 8 ? T_WG + 15360 * (ti - 2) : T_WD + 13824 * (ti - 8);
                    const int c0 = (ti >= 2 && ti < 8) ? boxcol : 72 * mem;
                    const int c1 = ti < 2 ? 256 * grp + 128 * ti : ti < 5 ? 192 * (ti - 2) : ti < 8 ? 192 * (ti - 5) : 288 * grp + 96 * (ti - 8);
                    tma2d(sb + off, tm, c0, c1, bar);
                    ti++;
                }
            }
            STAMP(2);
        }
        return;
    }

    const int g = lane >> 2, t = lane & 3;
    const uint32_t act = sb + OFF_ACT, red = sb + OFF_RED, stat = sb + OFF_STAT;
    const uint32_t act_row = act + warp * ACT_PITCH;

    uint32_t xpair = 0;
    uint32_t cv[9];
    {
        unsigned ep = 0;
        if (tid == 0) asm volatile("ld.relaxed.gpu.global.u32 %0, [%1];" : "=r"(ep) : "l"(&scr->epoch) : "memory");
        if (cta < 36) {
            const int sub = tid & 3, row = tid >> 2;
            const char* src = reinterpret_cast<const char*>(prm.wmod) + row * (6 * DM * 2) + ((sub >> 1) * DM + 16 * cta) * 2 + (sub & 1) * 16;
            const uint32_t dst = sb + P_A + row * 64 + ((sub ^ ((row >> 1) & 3)) << 4);
#pragma unroll
            for (int j = 0; j < 9; j++)
                asm volatile("cp.async.cg.shared.global [%0], [%1], 16;" ::"r"(dst + j * 64 * 64), "l"(src + (size_t)j * 64 * (6 * DM * 2)) : "memory");
        }
        if (cta < 36 || extra) {
            const uint32_t* crow = reinterpret_cast<const uint32_t*>(prm.c + warp * DM) + lane;
#pragma unroll
            for (int k = 0; k < 9; k++) cv[k] = __ldg(crow + 32 * k);
        }
        if (extra) {
#pragma unroll 1
            for (int i = tid; i < 2304; i += 256) ll_st(&scr->mod[i / 288][288 * (cta - NCTA) + i % 288], 0, 0);
        } else if (tid < 128) {
            ll_st(&scr->q[grp][tid >> 4][16 * mem + (tid & 15)], 0, 0);
            if (cta < 36 && tid < 24) ll_st128(&scr->h0[tid / 3][3 * cta + tid % 3][0], 0, 0, 0, 0);
        }
        if (cta < 36) {
            const uint32_t* xrow = reinterpret_cast<const uint32_t*>(prm.x + warp * DM) + lane;
            uint32_t xv[9];
#pragma unroll
            for (int k = 0; k < 9; k++) xv[k] = __ldg(xrow + 32 * k);
            if (tid < 64) xpair = __ldg(reinterpret_cast<const uint32_t*>(prm.x + (tid >> 3) * DM + 16 * cta) + (tid & 7));
            float mean, den;
            ln_stats<false>(xv, mean, den);
            if (lane == 0) sts64f(stat + 8 * warp, mean, den);
        }
        if (tid == 32) STAMP(44);
        if (tid == 0) sts32(stat + 64, ep + 1);
        if (tid == 0) STAMP(45);
    }
    asm volatile("bar.sync 2, 288;" ::: "memory");
    const uint32_t tag = lds32(stat + 64);
    if (tid == 0) STAMP(14);

    const int xcol = 1152 + DM * (cta - NCTA);
    auto issue_slice = [&](int it) {
#pragma unroll 1
        for (int p = 0; p < 3; p++) {
            const uint32_t bar = bars + 8 * (BAR_P + 3 * (it & 1) + p);
            mbar_expect_tx(bar, 12288);
            tma2d(sb + ((it & 1) ? P_B : P_A) + p * 12288, &tmMod, xcol + 32 * it, 192 * p, bar);
        }
    };
    if (extra && tid == 0) { issue_slice(0); issue_slice(1); }
    const int nit = extra ? 18 : cta < 36 ? 2 : 1;
#pragma unroll 1
    for (int it = 0; it < nit; it++) {
        const int st = it & 1;
        const bool crit = cta < 36 && it == 0, is_q = !extra && !crit;
        const bool stage = !extra || it == 0;
        uint32_t av[9];
        if (!is_q) {
#pragma unroll
            for (int k = 0; k < 9; k++) av[k] = pack_bf16(silu_f(bf_lo(cv[k])), silu_f(bf_hi(cv[k])));
        }
        if (crit) {
            asm volatile("cp.async.wait_all;" ::: "memory");
        } else {
#pragma unroll 1
            for (int p = 0; p < 3; p++) mbar_wait(bars + 8 * (BAR_P + 3 * st + p), (it >> 1) & 1);
        }
        if (tid == 0 && !extra) STAMP(15 + st);
        if (lane == 0 && is_q) STAMP(72 + warp);
        uint32_t hw[4][3];
        if (is_q) {
            const u64* hp = &scr->h0[warp][lane][0];
            const u64* hl = &scr->h0[warp][96 + (lane < 12 ? lane : 0)][0];
            int pit = 0;
            uint32_t bad;
            do {
                bad = 0;
#pragma unroll
                for (int k = 0; k < 4; k++) {
                    uint32_t tg;
                    ll_ld128(k < 3 ? hp + 64 * k : hl, hw[k][0], hw[k][1], hw[k][2], tg);
                    bad |= tg ^ tag;
                }
            } while (!poll_done(bad, pit));
        }
        if (lane == 0 && is_q) STAMP(64 + warp);
        if (it > 0) cbar();
        if (is_q) {
#pragma unroll
            for (int k = 0; k < 4; k++) {
                const int pk = lane + 32 * k, c = pk / 3, j = pk - 3 * c;
                if (k < 3 || lane < 12) {
                    const uint32_t a = act_row + 4 * (8 * c + 3 * j);
                    sts32(a, hw[k][0]); sts32(a + 4, hw[k][1]);
                    if (j < 2) sts32(a + 8, hw[k][2]);
                }
            }
        } else if (stage) {
#pragma unroll
            for (int k = 0; k < 9; k++) sts32(act_row + 4 * (lane + 32 * k), av[k]);
        }
        if (stage) cbar();
        if (tid == 0 && !extra) STAMP(is_q ? 4 : 3);
        {
            const int mt = warp & 1, kg = warp >> 1;
            const int rl = (lane & 7) + ((lane >> 4) << 3);
            const uint32_t aaddr = sb + (st ? P_B : P_A) + (144 * kg + rl) * 64 + (((2 * mt + ((lane >> 3) & 1)) ^ ((rl >> 1) & 3)) << 4);
            const uint32_t baddr = act + (lane & 7) * ACT_PITCH + ((lane >> 3) & 1) * 16 + 288 * kg;
            float c0[4] = {0.f, 0.f, 0.f, 0.f}, c1[4] = {0.f, 0.f, 0.f, 0.f};
#pragma unroll
            for (int i = 0; i < 9; i++) {
                uint32_t a[4], b0, b1;
                ldsm4t(a, aaddr + i * 16 * 64);
                ldsm2(b0, b1, baddr + i * 32);
                if (i & 1) mma16816(c1, a, b0, b1); else mma16816(c0, a, b0, b1);
            }
            const uint32_t dst = red + warp * 512 + g * 32 + t * 8;
            sts64f(dst, c0[0] + c1[0], c0[1] + c1[1]);
            sts64f(dst + 256, c0[2] + c1[2], c0[3] + c1[3]);
        }
        if (tid == 0 && is_q) STAMP(47);
        if (tid == 224 && is_q) STAMP(48);
        cbar();
        if (tid == 0 && is_q) STAMP(49);
        if (tid == 0) {
            if (extra) {
                if (it + 2 < nit) issue_slice(it + 2);
            } else if (st == 0) {
                mbar_arrive_n(bars + 8 * (BAR_EMPTY + 3), 4); mbar_arrive_n(bars + 8 * (BAR_EMPTY + 4), 4);
                if (cta >= 36) mbar_arrive_n(bars + 8 * (BAR_EMPTY + 5), 4);
            } else {
                mbar_arrive_n(bars + 8 * (BAR_EMPTY + 5), 4); mbar_arrive_n(bars + 8 * (BAR_EMPTY + 6), 4);
                mbar_arrive_n(bars + 8 * (BAR_EMPTY + 7), 4);
            }
        }
        if (tid < 128) {
            const int b = crit ? (tid >> 3) & 7 : tid >> 4, cp = crit ? tid & 7 : tid & 15;
            const uint32_t ra = red + (cp >> 3) * 512 + (2 * (cp & 7)) * 32 + b * 4;
            const float v0 = (ldsf(ra) + ldsf(ra + 1024)) + (ldsf(ra + 2048) + ldsf(ra + 3072));
            const float v1 = (ldsf(ra + 32) + ldsf(ra + 1056)) + (ldsf(ra + 2080) + ldsf(ra + 3104));
            uint32_t val = pack_bf16(v0, v1);
            if (crit) {
                const uint32_t ca = pack_bf16((ldsf(ra + 512) + ldsf(ra + 1536)) + (ldsf(ra + 2560) + ldsf(ra + 3584)),
                                              (ldsf(ra + 544) + ldsf(ra + 1568)) + (ldsf(ra + 2592) + ldsf(ra + 3616)));
                const float mean = ldsf(stat + 8 * b), den = ldsf(stat + 8 * b + 4);
                const uint32_t d = bf2_sub(xpair, pack_bf16(mean, mean));
                const uint32_t n = pack_bf16(__fdiv_rn(bf_lo(d), den), __fdiv_rn(bf_hi(d), den));
                val = bf2_add(bf2_mul(n, bf2_add(BF2_ONE, ca)), val);
                const uint32_t w1 = __shfl_down_sync(0xffffffffu, val, 1), w2 = __shfl_down_sync(0xffffffffu, val, 2);
                if (tid < 64 && cp % 3 == 0) ll_st128(&scr->h0[b][3 * cta + cp / 3][0], val, w1, cp < 6 ? w2 : 0u, tag);
            } else {
                ll_st(is_q ? &scr->q[grp][b][16 * mem + cp] : &scr->mod[b][288 * (cta - NCTA) + 16 * it + cp], val, tag);
            }
        }
        if (tid == 0 && !extra) STAMP(is_q ? 17 : 46);
    }
    if (extra) return;
    cbar();
    const uint32_t actb = sb + OFF_ACTB;
    const int rb = grp >> 1;
    const int rpair = 36 * mem + 18 * (grp & 1) + (lane < 18 ? lane : 0);
    uint32_t x_r = 0, ga_r = 0, gb_r = 0;
    uint32_t sbv[9], cbv[9];
#pragma unroll
    for (int k = 0; k < 9; k++) sbv[k] = cbv[k] = 0;

    float oacc[8][4];
#pragma unroll
    for (int m = 0; m < 8; m++) { oacc[m][0] = oacc[m][1] = oacc[m][2] = oacc[m][3] = 0.f; }
    float m0 = -INFINITY, m1 = -INFINITY, l0 = 0.f, l1 = 0.f;
    const float SC = 1.4426950408889634f;
    {
        uint32_t qf[16];
        {
            uint32_t qv[1];
            ll_poll<1, 0>(&scr->q[grp][mem][16 * warp + (lane & 15)], tag, qv);
            if (lane < 16) sts32(actb + 4 * (16 * warp + lane), qv[0]);
            cbar();
#pragma unroll
            for (int k = 0; k < 16; k++) qf[k] = lds32(actb + 4 * ((g & 1) * 64 + t + 4 * k));
        }
        if (tid == 0) STAMP(5);
        const int gi = warp >> 2, wq = warp & 3;
        const uint32_t offK = (16 * wq + (lane & 7) + (((lane >> 3) & 1) << 3)) * 128;
        const uint32_t offV = (16 * wq + (lane & 7) + ((lane >> 4) << 3)) * 128;
        const uint32_t xK = ((lane >> 4) ^ (lane & 7)) << 4, xV = (((lane >> 3) & 1) ^ (lane & 7)) << 4;
        int slot = (TILE0 + 2 * gi) % NSLOT, use = (TILE0 + 2 * gi) / NSLOT;
#pragma unroll 1
        for (int kb = gi; kb < NTILES / 2; kb += 2) {
            if (kb - gi == MID_KB) {
                if (warp == 7) {
                    x_r = __ldg(reinterpret_cast<const uint32_t*>(prm.x + rb * DM) + rpair);
                    uint32_t gg[2];
                    ll_poll<2, 864>(&scr->mod[rb][rpair], tag, gg);
                    ga_r = gg[0]; gb_r = gg[1];
                }
                {
                    const u64* mp = &scr->mod[warp][288 + 3 * lane];
                    int it = 0;
                    uint32_t bad;
                    do {
                        bad = 0;
#pragma unroll
                        for (int k = 0; k < 9; k++) {
                            uint32_t t0, t1;
                            ll_ld(mp + 96 * (k / 3) + k % 3, sbv[k], t0);
                            ll_ld(mp + 288 + 96 * (k / 3) + k % 3, cbv[k], t1);
                            bad |= (t0 ^ tag) | (t1 ^ tag);
                        }
                    } while (!poll_done(bad, it));
#pragma unroll
                    for (int k = 0; k < 9; k++) cbv[k] = bf2_add(BF2_ONE, cbv[k]);
                }
                if (tid < 128) ll_st(&scr->o[grp][mem][tid], 0, 0);
                if (tid < 144) ll_st(&scr->hh[grp][18 * mem][0] + tid, 0, 0);
                if (tid < 6) ll_st128(&scr->x1[rb][12 * mem + 6 * (grp & 1) + tid][0], 0, 0, 0, 0);
#pragma unroll 1
                for (int i = tid; i < 576; i += 256) {
                    const int kq = i / 36;
                    u64* pp = &scr->p1[mem][kq][grp][i - 36 * kq];
                    ll_st(pp, 0, 0); ll_st(pp + P2_MINUS_P1, 0, 0);
                }
            }
            const uint32_t kt = sb + slot * SLOT + offK;
            mbar_wait(bars + 8 * (BAR_FULL + slot), use & 1);
            float sa[4] = {0.f, 0.f, 0.f, 0.f}, sc2[4] = {0.f, 0.f, 0.f, 0.f};
#pragma unroll
            for (int ks = 0; ks < 8; ks++) {
                uint32_t a[4];
                ldsm4(a, kt + (ks >> 2) * 8192 + (xK ^ ((ks & 3) << 5)));
                if (ks & 1) mma16816(sc2, a, qf[2 * ks], qf[2 * ks + 1]); else mma16816(sa, a, qf[2 * ks], qf[2 * ks + 1]);
            }
            __syncwarp();
            if (lane == 0) mbar_arrive(bars + 8 * (BAR_EMPTY + slot));
            const uint32_t r01 = pack_bf16(sa[0] + sc2[0], sa[1] + sc2[1]), r23 = pack_bf16(sa[2] + sc2[2], sa[3] + sc2[3]);
            const float RS = 0.08838834764831845f;
            const uint32_t u01 = pack_bf16(bf_lo(r01) * RS, bf_hi(r01) * RS), u23 = pack_bf16(bf_lo(r23) * RS, bf_hi(r23) * RS);
            const float s0 = bf_lo(u01), s1 = bf_hi(u01), s2 = bf_lo(u23), s3 = bf_hi(u23);
            const bool grow = (s0 > m0) || (s2 > m0) || (s1 > m1) || (s3 > m1);
            if (__any_sync(0xffffffffu, grow)) {
                float n0 = fmaxf(s0, s2), n1 = fmaxf(s1, s3);
#pragma unroll
                for (int o = 4; o < 32; o <<= 1) {
                    n0 = fmaxf(n0, __shfl_xor_sync(0xffffffffu, n0, o));
                    n1 = fmaxf(n1, __shfl_xor_sync(0xffffffffu, n1, o));
                }
                n0 = fmaxf(n0, m0); n1 = fmaxf(n1, m1);
                const float a0 = ex2((m0 - n0) * SC), a1 = ex2((m1 - n1) * SC);
                m0 = n0; m1 = n1; l0 *= a0; l1 *= a1;
#pragma unroll
                for (int m = 0; m < 8; m++) { oacc[m][0] *= a0; oacc[m][1] *= a1; oacc[m][2] *= a0; oacc[m][3] *= a1; }
            }
            const float mc0 = m0 * SC, mc1 = m1 * SC;
            const float p0 = ex2(fmaf(s0, SC, -mc0)), p1 = ex2(fmaf(s1, SC, -mc1));
            const float p2 = ex2(fmaf(s2, SC, -mc0)), p3 = ex2(fmaf(s3, SC, -mc1));
            l0 += p0 + p2; l1 += p1 + p3;
            const uint32_t pb0 = movmat(pack_bf16(p0, p1)), pb1 = movmat(pack_bf16(p2, p3));
            const uint32_t vt = sb + (slot + 1) * SLOT + offV;
            mbar_wait(bars + 8 * (BAR_FULL + slot + 1), use & 1);
#pragma unroll
            for (int mt = 0; mt < 8; mt++) {
                uint32_t a[4];
                ldsm4t(a, vt + (mt >> 2) * 8192 + (xV ^ ((mt & 3) << 5)));
                mma16816(oacc[mt], a, pb0, pb1);
            }
            __syncwarp();
            if (lane == 0) mbar_arrive(bars + 8 * (BAR_EMPTY + slot + 1));
            slot += 4;
            if (slot >= NSLOT) { slot -= NSLOT; use++; }
        }
    }
    if (tid == 0) STAMP(6);
    if (tid == 128) STAMP(26);

    {
#pragma unroll
        for (int o = 4; o < 32; o <<= 1) { l0 += __shfl_xor_sync(0xffffffffu, l0, o); l1 += __shfl_xor_sync(0xffffffffu, l1, o); }
        const uint32_t ro = red + warp * 1024 + g * 8;
#pragma unroll
        for (int mt = 0; mt < 8; mt++) {
            if (t == (mt >> 1)) {
                sts64f(ro + mt * 128, oacc[mt][0], oacc[mt][1]);
                sts64f(ro + mt * 128 + 64, oacc[mt][2], oacc[mt][3]);
            }
        }
        if (lane == 0) sts128f(red + 8192 + warp * 16, m0, m1, l0, l1);
        u64* po = &scr->o[grp][mem][tid & 127];
        uint32_t rv = red + (tid & 63) * 16;
        PIN64(po); PIN32(rv);
        cbar();
        if (tid < 128) {
            const bool h = tid >= 64;
            float mw[8], lw[8], v0[8], v1[8];
#pragma unroll
            for (int w = 0; w < 8; w++) {
                const float4 a = lds128f(red + 8192 + w * 16), v = lds128f(rv + w * 1024);
                mw[w] = h ? a.y : a.x; lw[w] = h ? a.w : a.z;
                v0[w] = h ? v.y : v.x; v1[w] = h ? v.w : v.z;
            }
            const float M = fmaxf(fmaxf(fmaxf(mw[0], mw[1]), fmaxf(mw[2], mw[3])), fmaxf(fmaxf(mw[4], mw[5]), fmaxf(mw[6], mw[7])));
            float L = 0.f, o0 = 0.f, o1 = 0.f;
#pragma unroll
            for (int w = 0; w < 8; w++) {
                const float f = ex2((mw[w] - M) * SC);
                L = fmaf(f, lw[w], L); o0 = fmaf(f, v0[w], o0); o1 = fmaf(f, v1[w], o1);
            }
            const float inv = __fdividef(1.f, L);
            ll_st(po, pack_bf16(o0 * inv, o1 * inv), tag);
        }
    }
    if (tid == 0) STAMP(7);
    const int rl = (lane & 7) + ((lane >> 4) << 3);
    const uint32_t a72 = sb + rl * 144 + (2 * warp + ((lane >> 3) & 1)) * 16;
    u64 *pw0, *pw1;
    {
        const int c0 = min(16 * warp + g, 71), c1 = min(16 * warp + g + 8, 71);
        u64* pb = &scr->p1[mem][4 * t][grp][0];
        pw0 = pb + (c0 >= 36 ? 576 + c0 - 36 : c0);
        pw1 = pb + (c1 >= 36 ? 576 + c1 - 36 : c1);
    }
    const bool hi_ok = warp < 4;
    {
        uint32_t wa[16][4];
        mbar_wait(bars + 8 * (BAR_T + 0), 0);
        mbar_wait(bars + 8 * (BAR_T + 1), 0);
        gemv72_load<16>(wa, a72 + T_WO);
        if (tid == 0) STAMP(18);
        const u64* po = &scr->o[grp][warp][lane];
        uint32_t dst = actb + warp * ACTB_O_PITCH + lane * 4;
        uint32_t baddr = actb + (lane & 7) * ACTB_O_PITCH + (lane >> 3) * 16;
        PIN64(pw0); PIN64(pw1); PIN32(dst); PIN32(baddr);
        uint32_t ov[4];
        ll_poll<4, 32>(po, tag, ov);
        if (tid == 0) STAMP(53);
        if (tid == 128) STAMP(54);
        if (tid == 224) STAMP(55);
#pragma unroll
        for (int k = 0; k < 4; k++) sts32(dst + 128 * k, ov[k]);
        cbar();
        if (tid == 0) STAMP(8);
        if (warp < 5) gemv72_run<16>(wa, baddr, pw0, pw1, hi_ok, tag);
        if (tid == 0) STAMP(21);
    }
    uint32_t x1_r = 0;
    const u64* pr = &scr->p1[mem][grp][2 * warp][lane < 18 ? 2 * lane : 0];
    {
        u64* px = &scr->x1[rb][12 * mem + 6 * (grp & 1) + (lane < 6 ? lane : 0)][0];
        int src = lane < 6 ? 3 * lane : 0;
        PIN64(px); PIN32(src);
        float a0 = 0.f, a1 = 0.f;
        reduce16(pr, red, warp, lane, tag, a0, a1);
        if (warp == 7) {
            x1_r = pack_bf16(fmaf(bf_lo(ga_r), a0, bf_lo(x_r)), fmaf(bf_hi(ga_r), a1, bf_hi(x_r)));
            const uint32_t w0 = __shfl_sync(0xffffffffu, x1_r, src), w1 = __shfl_sync(0xffffffffu, x1_r, src + 1),
                           w2 = __shfl_sync(0xffffffffu, x1_r, src + 2);
            if (lane < 6) ll_st128(px, w0, w1, w2, tag);
            if (lane == 0) STAMP(9);
        }
    }
    {
        const int mat = warp >> 2, kg = warp & 3;
#pragma unroll 1
        for (int p = 0; p < 3; p++) mbar_wait(bars + 8 * (BAR_T + 2 + 3 * mat + p), 0);
        if (tid == 0) STAMP(19);
        const uint32_t aaddr = sb + (mat ? T_WU : T_WG) + (144 * kg + rl) * 80 + ((lane >> 3) & 1) * 16;
        uint32_t wa[9][3][4];
#pragma unroll
        for (int i = 0; i < 6; i++)
#pragma unroll
            for (int m = 0; m < 3; m++) ldsm4t(wa[i][m], aaddr + i * 16 * 80 + m * 32);

        const u64* xp = &scr->x1[warp][lane][0];
        uint32_t adst = act_row + 12 * lane;
        uint32_t baddr = act + (lane & 7) * ACT_PITCH + (lane >> 3) * 16 + 288 * kg;
        PIN32(adst); PIN32(baddr);
        asm volatile("bar.sync 4, 256;" ::: "memory");
        uint32_t xv[9];
        {
            int it = 0;
            uint32_t bad;
            do {
                bad = 0;
#pragma unroll
                for (int k = 0; k < 3; k++) {
                    uint32_t tg;
                    ll_ld128(xp + 64 * k, xv[3 * k], xv[3 * k + 1], xv[3 * k + 2], tg);
                    bad |= tg ^ tag;
                }
            } while (!poll_done(bad, it));
        }
        if (tid == 0) STAMP(23);
        float mean, den;
        ln_stats<true>(xv, mean, den);
        const uint32_t m2 = pack_bf16(mean, mean);
        float rinv;
        asm("rcp.approx.f32 %0, %1;" : "=f"(rinv) : "f"(den));
#pragma unroll
        for (int k = 0; k < 9; k++) sts32(adst + 384 * (k / 3) + 4 * (k % 3), ln_mod2(xv[k], m2, rinv, cbv[k], sbv[k]));
#pragma unroll
        for (int i = 6; i < 9; i++)
#pragma unroll
            for (int m = 0; m < 3; m++) ldsm4t(wa[i][m], aaddr + i * 16 * 80 + m * 32);
        uint32_t rdst = red + warp * 1536 + g * 32 + t * 8;
        uint32_t rsrc = red + (((36 * cta) & 7) + 2 * (tid >> 3)) * 32 + (tid & 7) * 4;
        u64* ph = &scr->hh[grp][18 * mem][0] + (tid < 144 ? tid : 0);
        PIN32(rdst); PIN32(rsrc); PIN64(ph);
        cbar();
        if (tid == 0) STAMP(10);
        float c[2][3][4];
#pragma unroll
        for (int m = 0; m < 3; m++)
#pragma unroll
            for (int j = 0; j < 4; j++) c[0][m][j] = c[1][m][j] = 0.f;
#pragma unroll
        for (int i = 0; i < 9; i += 2) {
            uint32_t b[4];
            ldsm4(b, baddr + i * 32);
#pragma unroll
            for (int m = 0; m < 3; m++) {
                mma16816(c[0][m], wa[i][m], b[0], b[1]);
                if (i + 1 < 9) mma16816(c[1][m], wa[i + 1][m], b[2], b[3]);
            }
        }
#pragma unroll
        for (int m = 0; m < 3; m++) {
            sts64f(rdst + m * 512, c[0][m][0] + c[1][m][0], c[0][m][1] + c[1][m][1]);
            sts64f(rdst + m * 512 + 256, c[0][m][2] + c[1][m][2], c[0][m][3] + c[1][m][3]);
        }
        if (tid == 0) STAMP(24);
        cbar();
        if (tid < 144) {
            float r[2];
#pragma unroll
            for (int e = 0; e < 2; e++) {
                const uint32_t a = rsrc + 32 * e;
                const float gg = (ldsf(a) + ldsf(a + 1536)) + (ldsf(a + 3072) + ldsf(a + 4608));
                const float uu = (ldsf(a + 6144) + ldsf(a + 7680)) + (ldsf(a + 9216) + ldsf(a + 10752));
                r[e] = gelu_f(gg) * uu;
            }
            ll_st(ph, pack_bf16(r[0], r[1]), tag);
        }
        if (cta == 0 && tid == 255) {
            asm volatile("st.relaxed.gpu.global.u32 [%0], %1;" ::"l"(&scr->epoch), "r"(tag) : "memory");
            asm volatile("st.relaxed.gpu.global.u32 [%0], %1;" ::"l"(&scr->prog), "r"(0u) : "memory");
        }
    }
    if (tid == 0) STAMP(11);
    {
        uint32_t wa[18][4];
#pragma unroll 1
        for (int p = 0; p < 3; p++) mbar_wait(bars + 8 * (BAR_T + 8 + p), 0);
        gemv72_load<18>(wa, a72 + T_WD);
        if (tid == 0) STAMP(20);
        const u64* hp = &scr->hh[grp][0][0] + tid;
        const u64* hl = &scr->hh[grp][128][0] + (tid & 127);
        uint32_t dst = actb + (tid & 7) * ACTB_H_PITCH + (tid >> 3) * 4;
        uint32_t dl = actb + (tid & 7) * ACTB_H_PITCH + (128 + ((tid & 127) >> 3)) * 4;
        uint32_t baddr = actb + (lane & 7) * ACTB_H_PITCH + (lane >> 3) * 16;
        u64 *q0 = pw0 + P2_MINUS_P1, *q1 = pw1 + P2_MINUS_P1;
        PIN32(dst); PIN32(dl); PIN32(baddr); PIN64(q0); PIN64(q1);
        uint32_t hv[5];
        {
            int it = 0;
            uint32_t bad;
            do {
                bad = 0;
#pragma unroll
                for (int k = 0; k < 5; k++) { uint32_t tg; ll_ld(k < 4 ? hp + 256 * k : hl, hv[k], tg); bad |= tg ^ tag; }
            } while (!poll_done(bad, it));
        }
#pragma unroll
        for (int k = 0; k < 4; k++) sts32(dst + 128 * k, hv[k]);
        sts32(dl, hv[4]);
        cbar();
        if (tid == 0) STAMP(12);
        if (warp < 5) gemv72_run<18>(wa, baddr, q0, q1, hi_ok, tag);
        if (tid == 0) STAMP(22);
    }
    {
        uint32_t* po = reinterpret_cast<uint32_t*>(prm.out + rb * DM) + rpair;
        PIN64(po);
        float a0 = 0.f, a1 = 0.f;
        reduce16(pr + P2_MINUS_P1, red, warp, lane, tag, a0, a1);
        if (warp == 7) {
            if (lane < 18) *po = pack_bf16(fmaf(bf_lo(gb_r), a0, bf_lo(x1_r)), fmaf(bf_hi(gb_r), a1, bf_hi(x1_r)));
            if (lane == 0) STAMP(13);
        }
    }
}

typedef CUresult (*EncodeFn)(CUtensorMap*, CUtensorMapDataType, cuuint32_t, void*, const cuuint64_t*, const cuuint64_t*,
                             const cuuint32_t*, const cuuint32_t*, CUtensorMapInterleave, CUtensorMapSwizzle,
                             CUtensorMapL2promotion, CUtensorMapFloatOOBfill);

void make_map2d(EncodeFn enc, CUtensorMap* m, const void* ptr, uint64_t cols, uint64_t rows, uint32_t bc, uint32_t br,
                CUtensorMapSwizzle sw, CUtensorMapL2promotion pr) {
    cuuint64_t dims[2] = {cols, rows};
    cuuint64_t strides[1] = {cols * 2};
    cuuint32_t box[2] = {bc, br};
    cuuint32_t es[2] = {1, 1};
    enc(m, CU_TENSOR_MAP_DATA_TYPE_BFLOAT16, 2, const_cast<void*>(ptr), dims, strides, box, es,
        CU_TENSOR_MAP_INTERLEAVE_NONE, sw, pr, CU_TENSOR_MAP_FLOAT_OOB_FILL_NONE);
}
void make_map_kv(EncodeFn enc, CUtensorMap* m, const void* ptr) {
    cuuint64_t dims[3] = {64, (cuuint64_t)NB * 16 * SK, 2};
    cuuint64_t strides[2] = {256, 128};
    cuuint32_t box[3] = {64, 64, 2};
    cuuint32_t es[3] = {1, 1, 1};
    enc(m, CU_TENSOR_MAP_DATA_TYPE_BFLOAT16, 3, const_cast<void*>(ptr), dims, strides, box, es,
        CU_TENSOR_MAP_INTERLEAVE_NONE, CU_TENSOR_MAP_SWIZZLE_128B, CU_TENSOR_MAP_L2_PROMOTION_L2_256B,
        CU_TENSOR_MAP_FLOAT_OOB_FILL_NONE);
}

}

extern "C" void kernel_launch(void* const* d_in, const int* in_sizes, int n_in, void* d_out, int out_size) {
    (void)in_sizes; (void)n_in; (void)out_size;
    static EncodeFn enc = nullptr;
    static Scratch* scr = nullptr;
    if (!enc) {
        void* fn = nullptr;
        cudaDriverEntryPointQueryResult qr;
        cudaGetDriverEntryPoint("cuTensorMapEncodeTiled", &fn, cudaEnableDefault, &qr);
        enc = (EncodeFn)fn;
        cudaGetSymbolAddress((void**)&scr, g_scr);
        cudaFuncSetAttribute(adaln_gqa_geglu_decode_kernel, cudaFuncAttributeMaxDynamicSharedMemorySize, SMEM_BYTES);
    }
    CUtensorMap tmK, tmV, tmMod, tmWq, tmWo, tmWg, tmWu, tmWd;
    make_map_kv(enc, &tmK, d_in[1]);
    make_map_kv(enc, &tmV, d_in[2]);
    make_map2d(enc, &tmMod, d_in[10], 6 * DM, DM, 32, 192, CU_TENSOR_MAP_SWIZZLE_64B, CU_TENSOR_MAP_L2_PROMOTION_L2_128B);
    make_map2d(enc, &tmWq, d_in[3], 4096, DM, 32, 192, CU_TENSOR_MAP_SWIZZLE_64B, CU_TENSOR_MAP_L2_PROMOTION_L2_128B);
    make_map2d(enc, &tmWo, d_in[4], DM, 4096, 72, 128, CU_TENSOR_MAP_SWIZZLE_NONE, CU_TENSOR_MAP_L2_PROMOTION_L2_128B);
    make_map2d(enc, &tmWg, d_in[6], DF, DM, 40, 192, CU_TENSOR_MAP_SWIZZLE_NONE, CU_TENSOR_MAP_L2_PROMOTION_L2_128B);
    make_map2d(enc, &tmWu, d_in[7], DF, DM, 40, 192, CU_TENSOR_MAP_SWIZZLE_NONE, CU_TENSOR_MAP_L2_PROMOTION_L2_128B);
    make_map2d(enc, &tmWd, d_in[8], DM, DF, 72, 96, CU_TENSOR_MAP_SWIZZLE_NONE, CU_TENSOR_MAP_L2_PROMOTION_L2_128B);
    Params prm;
    prm.x = (const __nv_bfloat16*)d_in[0];
    prm.c = (const __nv_bfloat16*)d_in[9];
    prm.wmod = (const __nv_bfloat16*)d_in[10];
    prm.out = (__nv_bfloat16*)d_out;
    prm.scr = scr;
    adaln_gqa_geglu_decode_kernel<<<NCTA + NXTRA, NTHREADS, SMEM_BYTES, cudaStreamPerThread>>>(prm, tmK, tmV, tmMod, tmWq, tmWo, tmWg, tmWu, tmWd);
}
```

```cpp
#include <cuda_runtime.h>
#include <cuda_bf16.h>
#include <cuda.h>
#include <stdint.h>
#include <stddef.h>

namespace {

typedef unsigned long long u64;

constexpr int NB = 8;
constexpr int DM = 576;
constexpr int SK = 8192;
constexpr int DF = 4608;
constexpr int NCTA = 128;
constexpr int NXTRA = 4;
constexpr int NTHREADS = 288;

constexpr int NSLOT = 12;
constexpr int SLOT = 16384;
constexpr int RING = NSLOT * SLOT;
constexpr int P_REG = DM * 64;
constexpr int P_A = 3 * SLOT;
constexpr int P_B = P_A + P_REG;
constexpr int T_WO = 0;
constexpr int T_WG = T_WO + 256 * 144;
constexpr int T_WU = T_WG + DM * 80;
constexpr int T_WD = T_WU + DM * 80;
constexpr int T_END = T_WD + 288 * 144;
static_assert(T_END <= RING, "tail overlay");
static_assert(P_B + P_REG <= 8 * SLOT, "prologue overlay");
constexpr int ACT_PITCH = 1168;
constexpr int OFF_ACT = RING;
constexpr int OFF_RED = OFF_ACT + NB * ACT_PITCH;
constexpr int RED_BYTES = 12288 + 256;
constexpr int ACTB_O_PITCH = 528;
constexpr int ACTB_H_PITCH = 592;
constexpr int OFF_ACTB = OFF_RED + RED_BYTES;
constexpr int OFF_STAT = OFF_ACTB + NB * ACTB_H_PITCH;
constexpr int OFF_BAR = OFF_STAT + 128;
constexpr int BAR_FULL = 0, BAR_EMPTY = NSLOT, BAR_P = 2 * NSLOT, BAR_T = BAR_P + 6;
constexpr int NT_PIECES = 11;
constexpr int NBARS = BAR_T + NT_PIECES;
constexpr int OFF_Q = OFF_BAR + NBARS * 8;
constexpr int SMEM_USED = OFF_Q + 16 * 8;
constexpr int SMEM_BYTES = SMEM_USED + 1024;
static_assert(SMEM_BYTES <= 232448, "smem");

constexpr int NTILES = 256;
constexpr int TILE0 = 8;
constexpr int TILE_END = TILE0 + NTILES;
constexpr int LAST_USE = (TILE_END - 1) / NSLOT;
static_assert(TILE_END % NSLOT == 0, "last round must end with the last slot");

#define PACE_D0 4
#define PACE_GAIN 6
#define PACE_BIAS 0
#define PACE_DMIN 1
#define PACE_DMAX 8
#define PACE_DSTART 3
#define MID_KB 64
#define START_TILES 2
#define WIN_T 40000

constexpr int SPIN_LIMIT = 1 << 21;

struct Scratch {
    u64 h0[NB][128][2];
    u64 mod[NB][1152];
    u64 q[16][NB][128];
    u64 o[16][NB][128];
    u64 p1[8][16][16][36];
    u64 x1[NB][96][2];
    u64 hh[16][144][NB];
    u64 p2[8][16][16][36];
    unsigned int epoch, pad0[31];
    unsigned int prog, pad1[31];
};
__device__ __align__(1024) Scratch g_scr;
constexpr int P2_MINUS_P1 = (int)((offsetof(Scratch, p2) - offsetof(Scratch, p1)) / 8);

#define PIN32(x) asm volatile("" : "+r"(x))
#define PIN64(x) asm volatile("" : "+l"(x))

__device__ __forceinline__ uint32_t smem_u32(const void* p) { return (uint32_t)__cvta_generic_to_shared(p); }
__device__ __forceinline__ void sts32(uint32_t a, uint32_t v) { asm volatile("st.shared.b32 [%0], %1;" ::"r"(a), "r"(v) : "memory"); }
__device__ __forceinline__ void sts64f(uint32_t a, float x, float y) { asm volatile("st.shared.v2.f32 [%0], {%1, %2};" ::"r"(a), "f"(x), "f"(y) : "memory"); }
__device__ __forceinline__ void sts128f(uint32_t a, float x, float y, float z, float w) {
    asm volatile("st.shared.v4.f32 [%0], {%1, %2, %3, %4};" ::"r"(a), "f"(x), "f"(y), "f"(z), "f"(w) : "memory");
}
__device__ __forceinline__ uint32_t lds32(uint32_t a) { uint32_t v; asm volatile("ld.shared.b32 %0, [%1];" : "=r"(v) : "r"(a)); return v; }
__device__ __forceinline__ float ldsf(uint32_t a) { float v; asm volatile("ld.shared.f32 %0, [%1];" : "=f"(v) : "r"(a)); return v; }
__device__ __forceinline__ float4 lds128f(uint32_t a) {
    float4 v;
    asm volatile("ld.shared.v4.f32 {%0, %1, %2, %3}, [%4];" : "=f"(v.x), "=f"(v.y), "=f"(v.z), "=f"(v.w) : "r"(a));
    return v;
}

__device__ __forceinline__ void mbar_init(uint32_t bar, uint32_t cnt) {
    asm volatile("mbarrier.init.shared::cta.b64 [%0], %1;" ::"r"(bar), "r"(cnt) : "memory");
}
__device__ __forceinline__ void mbar_expect_tx(uint32_t bar, uint32_t bytes) {
    asm volatile("mbarrier.arrive.expect_tx.shared::cta.b64 _, [%0], %1;" ::"r"(bar), "r"(bytes) : "memory");
}
__device__ __forceinline__ void mbar_arrive(uint32_t bar) {
    asm volatile("mbarrier.arrive.shared::cta.b64 _, [%0];" ::"r"(bar) : "memory");
}
__device__ __forceinline__ void mbar_arrive_n(uint32_t bar, uint32_t n) {
    asm volatile("mbarrier.arrive.shared::cta.b64 _, [%0], %1;" ::"r"(bar), "r"(n) : "memory");
}
__device__ __forceinline__ void mbar_wait(uint32_t bar, uint32_t parity) {
    asm volatile(
        "{\n.reg .pred p;\n.reg .u32 n;\nmov.u32 n, 0;\n"
        "W: mbarrier.try_wait.parity.shared::cta.b64 p, [%0], %1;\n"
        "@p bra D;\nadd.u32 n, n, 1;\nsetp.lt.u32 p, n, %2;\n@p bra W;\ntrap;\nD:\n}"
        ::"r"(bar), "r"(parity), "n"(SPIN_LIMIT) : "memory");
}
__device__ __forceinline__ void cbar() { asm volatile("bar.sync 1, 256;" ::: "memory"); }

__device__ __forceinline__ void tma2d(uint32_t dst, const CUtensorMap* tm, int c0, int c1, uint32_t bar) {
    asm volatile("cp.async.bulk.tensor.2d.shared::cluster.global.mbarrier::complete_tx::bytes [%0], [%1, {%3, %4}], [%2];"
                 ::"r"(dst), "l"(tm), "r"(bar), "r"(c0), "r"(c1) : "memory");
}
__device__ __forceinline__ void tma3d_hint(uint32_t dst, const CUtensorMap* tm, int c0, int c1, int c2, uint32_t bar, uint64_t pol) {
    asm volatile("cp.async.bulk.tensor.3d.shared::cluster.global.mbarrier::complete_tx::bytes.L2::cache_hint [%0], [%1, {%3, %4, %5}], [%2], %6;"
                 ::"r"(dst), "l"(tm), "r"(bar), "r"(c0), "r"(c1), "r"(c2), "l"(pol) : "memory");
}
__device__ __forceinline__ void ldsm4(uint32_t (&r)[4], uint32_t a) {
    asm volatile("ldmatrix.sync.aligned.m8n8.x4.shared.b16 {%0,%1,%2,%3}, [%4];"
                 : "=r"(r[0]), "=r"(r[1]), "=r"(r[2]), "=r"(r[3]) : "r"(a));
}
__device__ __forceinline__ void ldsm4t(uint32_t (&r)[4], uint32_t a) {
    asm volatile("ldmatrix.sync.aligned.m8n8.x4.trans.shared.b16 {%0,%1,%2,%3}, [%4];"
                 : "=r"(r[0]), "=r"(r[1]), "=r"(r[2]), "=r"(r[3]) : "r"(a));
}
__device__ __forceinline__ void ldsm2(uint32_t& r0, uint32_t& r1, uint32_t a) {
    asm volatile("ldmatrix.sync.aligned.m8n8.x2.shared.b16 {%0,%1}, [%2];" : "=r"(r0), "=r"(r1) : "r"(a));
}
__device__ __forceinline__ void mma16816(float (&c)[4], const uint32_t (&a)[4], uint32_t b0, uint32_t b1) {
    asm volatile("mma.sync.aligned.m16n8k16.row.col.f32.bf16.bf16.f32 {%0,%1,%2,%3}, {%4,%5,%6,%7}, {%8,%9}, {%0,%1,%2,%3};"
                 : "+f"(c[0]), "+f"(c[1]), "+f"(c[2]), "+f"(c[3])
                 : "r"(a[0]), "r"(a[1]), "r"(a[2]), "r"(a[3]), "r"(b0), "r"(b1));
}
__device__ __forceinline__ uint32_t movmat(uint32_t a) {
    uint32_t d;
    asm volatile("movmatrix.sync.aligned.m8n8.trans.b16 %0, %1;" : "=r"(d) : "r"(a));
    return d;
}
__device__ __forceinline__ float ex2(float x) {
    float y;
    asm("ex2.approx.ftz.f32 %0, %1;" : "=f"(y) : "f"(x));
    return y;
}
__device__ __forceinline__ uint32_t pack_bf16(float lo, float hi) {
    __nv_bfloat162 v = __floats2bfloat162_rn(lo, hi);
    return *reinterpret_cast<uint32_t*>(&v);
}
__device__ __forceinline__ float bf_lo(uint32_t v) { return __uint_as_float(v << 16); }
__device__ __forceinline__ float bf_hi(uint32_t v) { return __uint_as_float(v & 0xffff0000u); }
__device__ __forceinline__ float rbf(float x) { return __bfloat162float(__float2bfloat16_rn(x)); }

__device__ __forceinline__ void ll_st(u64* p, uint32_t data, uint32_t tag) {
    asm volatile("{\n.reg .b64 v;\nmov.b64 v, {%1, %2};\nst.relaxed.gpu.global.b64 [%0], v;\n}" ::"l"(p), "r"(data), "r"(tag) : "memory");
}
__device__ __forceinline__ void ll_ld(const u64* p, uint32_t& data, uint32_t& tg) {
    asm volatile("{\n.reg .b64 v;\nld.relaxed.gpu.global.b64 v, [%2];\nmov.b64 {%0, %1}, v;\n}" : "=r"(data), "=r"(tg) : "l"(p) : "memory");
}
__device__ __forceinline__ void ll_ld2(const u64* p, uint32_t& d0, uint32_t& t0, uint32_t& d1, uint32_t& t1) {
    asm volatile("{\n.reg .b64 a, b;\nld.relaxed.gpu.global.v2.b64 {a, b}, [%4];\nmov.b64 {%0, %1}, a;\nmov.b64 {%2, %3}, b;\n}"
                 : "=r"(d0), "=r"(t0), "=r"(d1), "=r"(t1) : "l"(p) : "memory");
}
__device__ __forceinline__ void ll_st128(u64* p, uint32_t w0, uint32_t w1, uint32_t w2, uint32_t tag) {
    asm volatile("{\n.reg .b128 r;\n.reg .b64 lo, hi;\nmov.b64 lo, {%1, %2};\nmov.b64 hi, {%3, %4};\nmov.b128 r, {lo, hi};\n"
                 "st.relaxed.gpu.global.b128 [%0], r;\n}" ::"l"(p), "r"(w0), "r"(w1), "r"(w2), "r"(tag) : "memory");
}
__device__ __forceinline__ void ll_ld128(const u64* p, uint32_t& w0, uint32_t& w1, uint32_t& w2, uint32_t& tg) {
    asm volatile("{\n.reg .b128 r;\n.reg .b64 lo, hi;\nld.relaxed.gpu.global.b128 r, [%4];\nmov.b128 {lo, hi}, r;\n"
                 "mov.b64 {%0, %1}, lo;\nmov.b64 {%2, %3}, hi;\n}" : "=r"(w0), "=r"(w1), "=r"(w2), "=r"(tg) : "l"(p) : "memory");
}
__device__ __forceinline__ bool poll_done(uint32_t bad, int& it) {
    if (!__any_sync(0xffffffffu, bad != 0)) return true;
    if (++it > SPIN_LIMIT) __trap();
    return false;
}
template <int N, int STRIDE>
__device__ __forceinline__ void ll_poll(const u64* p, uint32_t tag, uint32_t (&out)[N]) {
    int it = 0;
    uint32_t bad;
    do {
        bad = 0;
#pragma unroll
        for (int i = 0; i < N; i++) { uint32_t tg; ll_ld(p + i * STRIDE, out[i], tg); bad |= tg ^ tag; }
    } while (!poll_done(bad, it));
}
__device__ __forceinline__ void reduce16(const u64* p, uint32_t buf, int warp, int lane, uint32_t tag, float& s0, float& s1) {
    uint32_t a0, a1, b0, b1;
    {
        int it = 0;
        uint32_t bad;
        do {
            uint32_t t0, t1, t2, t3;
            ll_ld2(p, a0, t0, a1, t1);
            ll_ld2(p + 36, b0, t2, b1, t3);
            bad = ((t0 ^ tag) | (t1 ^ tag)) | ((t2 ^ tag) | (t3 ^ tag));
        } while (!poll_done(bad, it));
    }
    if (lane < 18) sts64f(buf + (warp * 18 + lane) * 8, __uint_as_float(a0) + __uint_as_float(b0), __uint_as_float(a1) + __uint_as_float(b1));
    if (warp != 7) {
        asm volatile("bar.arrive 3, 256;" ::: "memory");
    } else {
        asm volatile("bar.sync 3, 256;" ::: "memory");
        float x[8], y[8];
        const uint32_t q = buf + (lane < 18 ? lane : 0) * 8;
#pragma unroll
        for (int w = 0; w < 8; w++) asm volatile("ld.shared.v2.f32 {%0, %1}, [%2];" : "=f"(x[w]), "=f"(y[w]) : "r"(q + w * 144));
        s0 = ((x[0] + x[1]) + (x[2] + x[3])) + ((x[4] + x[5]) + (x[6] + x[7]));
        s1 = ((y[0] + y[1]) + (y[2] + y[3])) + ((y[4] + y[5]) + (y[6] + y[7]));
    }
}

template <bool FAST>
__device__ __forceinline__ void ln_stats(const uint32_t (&v)[9], float& mean, float& den) {
    const float k = __shfl_sync(0xffffffffu, bf_lo(v[0]), 0);
    float s = 0.f, q = 0.f;
#pragma unroll
    for (int i = 0; i < 9; i++) {
        const float a = bf_lo(v[i]) - k, b = bf_hi(v[i]) - k;
        s += a + b;
        q = fmaf(a, a, fmaf(b, b, q));
    }
#pragma unroll
    for (int o = 16; o > 0; o >>= 1) { s += __shfl_xor_sync(0xffffffffu, s, o); q += __shfl_xor_sync(0xffffffffu, q, o); }
    const float md = s * (1.0f / DM);
    mean = rbf(k + md);
    const float ve = rbf(rbf(fmaxf(q * (1.0f / DM) - md * md, 0.f)) + 1e-5f);
    float r;
    if (FAST) asm("sqrt.approx.f32 %0, %1;" : "=f"(r) : "f"(ve)); else r = __fsqrt_rn(ve);
    den = rbf(r);
}
__device__ __forceinline__ uint32_t bf2_add(uint32_t a, uint32_t b) {
    uint32_t d; asm("add.rn.bf16x2 %0, %1, %2;" : "=r"(d) : "r"(a), "r"(b)); return d;
}
__device__ __forceinline__ uint32_t bf2_sub(uint32_t a, uint32_t b) {
    uint32_t d; asm("sub.rn.bf16x2 %0, %1, %2;" : "=r"(d) : "r"(a), "r"(b)); return d;
}
__device__ __forceinline__ uint32_t bf2_mul(uint32_t a, uint32_t b) {
    uint32_t d; asm("mul.rn.bf16x2 %0, %1, %2;" : "=r"(d) : "r"(a), "r"(b)); return d;
}
__device__ __forceinline__ uint32_t ln_mod2(uint32_t x, uint32_t m2, float rinv, uint32_t c1, uint32_t sh) {
    const uint32_t d = bf2_sub(x, m2);
    const uint32_t n = pack_bf16(bf_lo(d) * rinv, bf_hi(d) * rinv);
    return bf2_add(bf2_mul(n, c1), sh);
}
constexpr uint32_t BF2_ONE = 0x3f803f80u;
__device__ __forceinline__ float silu_f(float a) { return __fdividef(a, 1.f + __expf(-a)); }
__device__ __forceinline__ float gelu_f(float g) {
    const float z2 = 1.5957691216057308f * fmaf(0.044715f * g * g, g, g);
    return __fdividef(g, 1.f + __expf(-z2));
}

template <int KSTEPS>
__device__ __forceinline__ void gemv72_load(uint32_t (&a)[KSTEPS][4], uint32_t aaddr) {
#pragma unroll
    for (int i = 0; i < KSTEPS; i++) ldsm4t(a[i], aaddr + i * 16 * 144);
}
template <int KSTEPS>
__device__ __forceinline__ void gemv72_run(const uint32_t (&a)[KSTEPS][4], uint32_t baddr, u64* p0, u64* p1, bool hi_ok, uint32_t tag) {
    float c[4][4];
#pragma unroll
    for (int j = 0; j < 4; j++) c[j][0] = c[j][1] = c[j][2] = c[j][3] = 0.f;
#pragma unroll
    for (int i = 0; i < KSTEPS; i += 2) {
        uint32_t b[4];
        ldsm4(b, baddr + i * 32);
        mma16816(c[i & 3], a[i], b[0], b[1]);
        mma16816(c[(i + 1) & 3], a[i + 1], b[2], b[3]);
    }
    const float r0 = (c[0][0] + c[1][0]) + (c[2][0] + c[3][0]), r1 = (c[0][1] + c[1][1]) + (c[2][1] + c[3][1]);
    const float r2 = (c[0][2] + c[1][2]) + (c[2][2] + c[3][2]), r3 = (c[0][3] + c[1][3]) + (c[2][3] + c[3][3]);
    ll_st(p0, __float_as_uint(r0), tag); ll_st(p0 + 2 * 576, __float_as_uint(r1), tag);
    if (hi_ok) { ll_st(p1, __float_as_uint(r2), tag); ll_st(p1 + 2 * 576, __float_as_uint(r3), tag); }
}

struct Params {
    const __nv_bfloat16* x;
    const __nv_bfloat16* c;
    const __nv_bfloat16* wmod;
    __nv_bfloat16* out;
    Scratch* scr;
};

__global__ void __launch_bounds__(NTHREADS, 1)
adaln_gqa_geglu_decode_kernel(const Params prm,
                              const __grid_constant__ CUtensorMap tmK, const __grid_constant__ CUtensorMap tmV,
                              const __grid_constant__ CUtensorMap tmMod, const __grid_constant__ CUtensorMap tmWq,
                              const __grid_constant__ CUtensorMap tmWo, const __grid_constant__ CUtensorMap tmWg,
                              const __grid_constant__ CUtensorMap tmWu, const __grid_constant__ CUtensorMap tmWd) {
    extern __shared__ unsigned char smem_raw[];
    uint32_t sb = (smem_u32(smem_raw) + 1023u) & ~1023u;
    int tid = threadIdx.x, cta = blockIdx.x;
    Scratch* scr = prm.scr;
    PIN32(sb); PIN32(tid); PIN32(cta); PIN64(scr);
    const uint32_t bars = sb + OFF_BAR;
    const int warp = tid >> 5, lane = tid & 31;
    const int grp = cta >> 3, mem = cta & 7;
    const bool extra = cta >= NCTA;

    if (warp == 8) {
        if (lane < 8) {
            const CUtensorMap* tm = lane == 0 ? &tmMod : lane == 1 ? &tmWq : lane == 2 ? &tmK : lane == 3 ? &tmV
                                  : lane == 4 ? &tmWo : lane == 5 ? &tmWg : lane == 6 ? &tmWu : &tmWd;
            asm volatile("prefetch.tensormap [%0];" ::"l"(tm) : "memory");
        }
        if (lane == 0) {
#pragma unroll
            for (int s = 0; s < NBARS; s++) mbar_init(bars + 8 * s, (s >= BAR_EMPTY && s < BAR_P) ? 4 : 1);
#pragma unroll
            for (int s = 0; s < 8; s++) {
                mbar_arrive(bars + 8 * (BAR_FULL + s));
                if (s < 3 || (s >= 6 && cta >= 36)) mbar_arrive_n(bars + 8 * (BAR_EMPTY + s), 4);
            }
            asm volatile("fence.mbarrier_init.release.cluster;" ::: "memory");
        }
        __syncwarp();
        asm volatile("bar.arrive 2, 288;" ::: "memory");
        if (lane == 0 && !extra) {
            uint64_t pol;
            asm volatile("createpolicy.fractional.L2::evict_first.b64 %0, 1.0;" : "=l"(pol));
            const uint32_t fifo = sb + OFF_Q;
            const int row0 = (mem * 16 + grp) * SK;
            const int boxcol = (36 * cta) & ~7;
            int head = 0, tail = 0, inflight = 0;
            int pi = 0, tp = TILE0, ti = 0, freed = 0, slot = TILE0, use = 0, win = PACE_DSTART, own_at = 0;
            unsigned gpend = 0;
#pragma unroll 1
            while (true) {
                uint32_t bar, par = 0;
                int bytes, window, kind;
                if (pi < 3) {
                    kind = 0; bar = bars + 8 * (BAR_P + (cta < 36 ? 3 : 0) + pi); bytes = 12288; window = 1 << 30;
                } else if (tp < TILE_END) {
                    kind = 1;
                    if (use > 0) mbar_wait(bars + 8 * (BAR_EMPTY + slot), (use - 1) & 1);
                    if (PACE_GAIN > 0 && (tp & 1) == 0) {
                        if (tp >= TILE0 + 12) {
                            const int sc = (own_at * NCTA - (int)gpend - PACE_BIAS) * PACE_GAIN;
                            const int adj = sc >= 0 ? (sc + 2 * NCTA) / (4 * NCTA) : -((-sc + 2 * NCTA) / (4 * NCTA));
                            win = min(max(PACE_D0 - adj, PACE_DMIN), PACE_DMAX);
                        }
                        asm volatile("red.relaxed.gpu.global.add.u32 [%0], 1;" ::"l"(&scr->prog) : "memory");
                        own_at = ((tp - TILE0) >> 1) + 1;
                        asm volatile("ld.relaxed.gpu.global.u32 %0, [%1];" : "=r"(gpend) : "l"(&scr->prog) : "memory");
                    } else if (PACE_GAIN == 0 && tp >= TILE0 + 12) win = PACE_D0;
                    bar = bars + 8 * (BAR_FULL + slot); par = use & 1; bytes = SLOT; window = tp < TILE0 + START_TILES ? (1 << 30) : win * SLOT;
                } else if (ti < NT_PIECES) {
                    kind = 2;
                    bytes = ti < 2 ? 18432 : ti < 8 ? 15360 : 13824;
                    const int end = ti < 2 ? 18432 * (ti + 1) : ti < 8 ? T_WG + 15360 * (ti - 1) : T_WD + 13824 * (ti - 7);
                    while (freed * SLOT < end) { mbar_wait(bars + 8 * (BAR_EMPTY + freed), LAST_USE & 1); freed++; }
                    bar = bars + 8 * (BAR_T + ti);
                    window = WIN_T;
                } else break;
                while (head != tail && inflight + bytes > window) {
                    const uint32_t e = lds32(fifo + 8 * (head & 15));
                    mbar_wait(e & ~1u, e & 1u);
                    inflight -= (int)lds32(fifo + 8 * (head & 15) + 4);
                    head++;
                }
                sts32(fifo + 8 * (tail & 15), bar | par); sts32(fifo + 8 * (tail & 15) + 4, bytes);
                tail++; inflight += bytes;
                mbar_expect_tx(bar, bytes);
                if (kind == 0) {
                    tma2d(sb + (cta < 36 ? P_B : P_A) + pi * 12288, &tmWq, 32 * cta, 192 * pi, bar);
                    pi++;
                } else if (kind == 1) {
                    tma3d_hint(sb + slot * SLOT, (tp & 1) ? &tmV : &tmK, 0, row0 + ((tp - TILE0) >> 1) * 64, 0, bar, pol);
                    if (++slot == NSLOT) { slot = 0; use++; }
                    tp++;
                } else {
                    const CUtensorMap* tm = ti < 2 ? &tmWo : ti < 5 ? &tmWg : ti < 8 ? &tmWu : &tmWd;
                    const int off = ti < 2 ? 18432 * ti : ti < 8 ? T_WG + 15360 * (ti - 2) : T_WD + 13824 * (ti - 8);
                    const int c0 = (ti >= 2 && ti < 8) ? boxcol : 72 * mem;
                    const int c1 = ti < 2 ? 256 * grp + 128 * ti : ti < 5 ? 192 * (ti - 2) : ti < 8 ? 192 * (ti - 5) : 288 * grp + 96 * (ti - 8);
                    tma2d(sb + off, tm, c0, c1, bar);
                    ti++;
                }
            }
        }
        return;
    }

    const int g = lane >> 2, t = lane & 3;
    const uint32_t act = sb + OFF_ACT, red = sb + OFF_RED, stat = sb + OFF_STAT;
    const uint32_t act_row = act + warp * ACT_PITCH;

    uint32_t xpair = 0;
    uint32_t cv[9];
    {
        unsigned ep = 0;
        if (tid == 0) asm volatile("ld.relaxed.gpu.global.u32 %0, [%1];" : "=r"(ep) : "l"(&scr->epoch) : "memory");
        if (cta < 36) {
            const int sub = tid & 3, row = tid >> 2;
            const char* src = reinterpret_cast<const char*>(prm.wmod) + row * (6 * DM * 2) + ((sub >> 1) * DM + 16 * cta) * 2 + (sub & 1) * 16;
            const uint32_t dst = sb + P_A + row * 64 + ((sub ^ ((row >> 1) & 3)) << 4);
#pragma unroll
            for (int j = 0; j < 9; j++)
                asm volatile("cp.async.cg.shared.global [%0], [%1], 16;" ::"r"(dst + j * 64 * 64), "l"(src + (size_t)j * 64 * (6 * DM * 2)) : "memory");
        }
        if (cta < 36 || extra) {
            const uint32_t* crow = reinterpret_cast<const uint32_t*>(prm.c + warp * DM) + lane;
#pragma unroll
            for (int k = 0; k < 9; k++) cv[k] = __ldg(crow + 32 * k);
        }
        if (extra) {
#pragma unroll 1
            for (int i = tid; i < 2304; i += 256) ll_st(&scr->mod[i / 288][288 * (cta - NCTA) + i % 288], 0, 0);
        } else if (tid < 128) {
            ll_st(&scr->q[grp][tid >> 4][16 * mem + (tid & 15)], 0, 0);
            if (cta < 36 && tid < 24) ll_st128(&scr->h0[tid / 3][3 * cta + tid % 3][0], 0, 0, 0, 0);
        }
        if (cta < 36) {
            const uint32_t* xrow = reinterpret_cast<const uint32_t*>(prm.x + warp * DM) + lane;
            uint32_t xv[9];
#pragma unroll
            for (int k = 0; k < 9; k++) xv[k] = __ldg(xrow + 32 * k);
            if (tid < 64) xpair = __ldg(reinterpret_cast<const uint32_t*>(prm.x + (tid >> 3) * DM + 16 * cta) + (tid & 7));
            float mean, den;
            ln_stats<false>(xv, mean, den);
            if (lane == 0) sts64f(stat + 8 * warp, mean, den);
        }
        if (tid == 0) sts32(stat + 64, ep + 1);
    }
    asm volatile("bar.sync 2, 288;" ::: "memory");
    const uint32_t tag = lds32(stat + 64);

    const int xcol = 1152 + DM * (cta - NCTA);
    auto issue_slice = [&](int it) {
#pragma unroll 1
        for (int p = 0; p < 3; p++) {
            const uint32_t bar = bars + 8 * (BAR_P + 3 * (it & 1) + p);
            mbar_expect_tx(bar, 12288);
            tma2d(sb + ((it & 1) ? P_B : P_A) + p * 12288, &tmMod, xcol + 32 * it, 192 * p, bar);
        }
    };
    if (extra && tid == 0) { issue_slice(0); issue_slice(1); }
    const int nit = extra ? 18 : cta < 36 ? 2 : 1;
#pragma unroll 1
    for (int it = 0; it < nit; it++) {
        const int st = it & 1;
        const bool crit = cta < 36 && it == 0, is_q = !extra && !crit;
        const bool stage = !extra || it == 0;
        uint32_t av[9];
        if (!is_q) {
#pragma unroll
            for (int k = 0; k < 9; k++) av[k] = pack_bf16(silu_f(bf_lo(cv[k])), silu_f(bf_hi(cv[k])));
        }
        if (crit) {
            asm volatile("cp.async.wait_all;" ::: "memory");
        } else {
#pragma unroll 1
            for (int p = 0; p < 3; p++) mbar_wait(bars + 8 * (BAR_P + 3 * st + p), (it >> 1) & 1);
        }
        uint32_t hw[4][3];
        if (is_q) {
            const u64* hp = &scr->h0[warp][lane][0];
            const u64* hl = &scr->h0[warp][96 + (lane < 12 ? lane : 0)][0];
            int pit = 0;
            uint32_t bad;
            do {
                bad = 0;
#pragma unroll
                for (int k = 0; k < 4; k++) {
                    uint32_t tg;
                    ll_ld128(k < 3 ? hp + 64 * k : hl, hw[k][0], hw[k][1], hw[k][2], tg);
                    bad |= tg ^ tag;
                }
            } while (!poll_done(bad, pit));
        }
        if (it > 0) cbar();
        if (is_q) {
#pragma unroll
            for (int k = 0; k < 4; k++) {
                const int pk = lane + 32 * k, c = pk / 3, j = pk - 3 * c;
                if (k < 3 || lane < 12) {
                    const uint32_t a = act_row + 4 * (8 * c + 3 * j);
                    sts32(a, hw[k][0]); sts32(a + 4, hw[k][1]);
                    if (j < 2) sts32(a + 8, hw[k][2]);
                }
            }
        } else if (stage) {
#pragma unroll
            for (int k = 0; k < 9; k++) sts32(act_row + 4 * (lane + 32 * k), av[k]);
        }
        if (stage) cbar();
        {
            const int mt = warp & 1, kg = warp >> 1;
            const int rl = (lane & 7) + ((lane >> 4) << 3);
            const uint32_t aaddr = sb + (st ? P_B : P_A) + (144 * kg + rl) * 64 + (((2 * mt + ((lane >> 3) & 1)) ^ ((rl >> 1) & 3)) << 4);
            const uint32_t baddr = act + (lane & 7) * ACT_PITCH + ((lane >> 3) & 1) * 16 + 288 * kg;
            float c0[4] = {0.f, 0.f, 0.f, 0.f}, c1[4] = {0.f, 0.f, 0.f, 0.f};
#pragma unroll
            for (int i = 0; i < 9; i++) {
                uint32_t a[4], b0, b1;
                ldsm4t(a, aaddr + i * 16 * 64);
                ldsm2(b0, b1, baddr + i * 32);
                if (i & 1) mma16816(c1, a, b0, b1); else mma16816(c0, a, b0, b1);
            }
            const uint32_t dst = red + warp * 512 + g * 32 + t * 8;
            sts64f(dst, c0[0] + c1[0], c0[1] + c1[1]);
            sts64f(dst + 256, c0[2] + c1[2], c0[3] + c1[3]);
        }
        cbar();
        if (tid == 0) {
            if (extra) {
                if (it + 2 < nit) issue_slice(it + 2);
            } else if (st == 0) {
                mbar_arrive_n(bars + 8 * (BAR_EMPTY + 3), 4); mbar_arrive_n(bars + 8 * (BAR_EMPTY + 4), 4);
                if (cta >= 36) mbar_arrive_n(bars + 8 * (BAR_EMPTY + 5), 4);
            } else {
                mbar_arrive_n(bars + 8 * (BAR_EMPTY + 5), 4); mbar_arrive_n(bars + 8 * (BAR_EMPTY + 6), 4);
                mbar_arrive_n(bars + 8 * (BAR_EMPTY + 7), 4);
            }
        }
        if (tid < 128) {
            const int b = crit ? (tid >> 3) & 7 : tid >> 4, cp = crit ? tid & 7 : tid & 15;
            const uint32_t ra = red + (cp >> 3) * 512 + (2 * (cp & 7)) * 32 + b * 4;
            const float v0 = (ldsf(ra) + ldsf(ra + 1024)) + (ldsf(ra + 2048) + ldsf(ra + 3072));
            const float v1 = (ldsf(ra + 32) + ldsf(ra + 1056)) + (ldsf(ra + 2080) + ldsf(ra + 3104));
            uint32_t val = pack_bf16(v0, v1);
            if (crit) {
                const uint32_t ca = pack_bf16((ldsf(ra + 512) + ldsf(ra + 1536)) + (ldsf(ra + 2560) + ldsf(ra + 3584)),
                                              (ldsf(ra + 544) + ldsf(ra + 1568)) + (ldsf(ra + 2592) + ldsf(ra + 3616)));
                const float mean = ldsf(stat + 8 * b), den = ldsf(stat + 8 * b + 4);
                const uint32_t d = bf2_sub(xpair, pack_bf16(mean, mean));
                const uint32_t n = pack_bf16(__fdiv_rn(bf_lo(d), den), __fdiv_rn(bf_hi(d), den));
                val = bf2_add(bf2_mul(n, bf2_add(BF2_ONE, ca)), val);
                const uint32_t w1 = __shfl_down_sync(0xffffffffu, val, 1), w2 = __shfl_down_sync(0xffffffffu, val, 2);
                if (tid < 64 && cp % 3 == 0) ll_st128(&scr->h0[b][3 * cta + cp / 3][0], val, w1, cp < 6 ? w2 : 0u, tag);
            } else {
                ll_st(is_q ? &scr->q[grp][b][16 * mem + cp] : &scr->mod[b][288 * (cta - NCTA) + 16 * it + cp], val, tag);
            }
        }
    }
    if (extra) return;
    cbar();
    const uint32_t actb = sb + OFF_ACTB;
    const int rb = grp >> 1;
    const int rpair = 36 * mem + 18 * (grp & 1) + (lane < 18 ? lane : 0);
    uint32_t x_r = 0, ga_r = 0, gb_r = 0;
    uint32_t sbv[9], cbv[9];
#pragma unroll
    for (int k = 0; k < 9; k++) sbv[k] = cbv[k] = 0;

    float oacc[8][4];
#pragma unroll
    for (int m = 0; m < 8; m++) { oacc[m][0] = oacc[m][1] = oacc[m][2] = oacc[m][3] = 0.f; }
    float m0 = -INFINITY, m1 = -INFINITY, l0 = 0.f, l1 = 0.f;
    const float SC = 1.4426950408889634f;
    {
        uint32_t qf[16];
        {
            uint32_t qv[1];
            ll_poll<1, 0>(&scr->q[grp][mem][16 * warp + (lane & 15)], tag, qv);
            if (lane < 16) sts32(actb + 4 * (16 * warp + lane), qv[0]);
            cbar();
#pragma unroll
            for (int k = 0; k < 16; k++) qf[k] = lds32(actb + 4 * ((g & 1) * 64 + t + 4 * k));
        }
        const int gi = warp >> 2, wq = warp & 3;
        const uint32_t offK = (16 * wq + (lane & 7) + (((lane >> 3) & 1) << 3)) * 128;
        const uint32_t offV = (16 * wq + (lane & 7) + ((lane >> 4) << 3)) * 128;
        const uint32_t xK = ((lane >> 4) ^ (lane & 7)) << 4, xV = (((lane >> 3) & 1) ^ (lane & 7)) << 4;
        int slot = (TILE0 + 2 * gi) % NSLOT, use = (TILE0 + 2 * gi) / NSLOT;
#pragma unroll 1
        for (int kb = gi; kb < NTILES / 2; kb += 2) {
            if (kb - gi == MID_KB) {
                if (warp == 7) {
                    x_r = __ldg(reinterpret_cast<const uint32_t*>(prm.x + rb * DM) + rpair);
                    uint32_t gg[2];
                    ll_poll<2, 864>(&scr->mod[rb][rpair], tag, gg);
                    ga_r = gg[0]; gb_r = gg[1];
                }
                {
                    const u64* mp = &scr->mod[warp][288 + 3 * lane];
                    int it = 0;
                    uint32_t bad;
                    do {
                        bad = 0;
#pragma unroll
                        for (int k = 0; k < 9; k++) {
                            uint32_t t0, t1;
                            ll_ld(mp + 96 * (k / 3) + k % 3, sbv[k], t0);
                            ll_ld(mp + 288 + 96 * (k / 3) + k % 3, cbv[k], t1);
                            bad |= (t0 ^ tag) | (t1 ^ tag);
                        }
                    } while (!poll_done(bad, it));
#pragma unroll
                    for (int k = 0; k < 9; k++) cbv[k] = bf2_add(BF2_ONE, cbv[k]);
                }
                if (tid < 128) ll_st(&scr->o[grp][mem][tid], 0, 0);
                if (tid < 144) ll_st(&scr->hh[grp][18 * mem][0] + tid, 0, 0);
                if (tid < 6) ll_st128(&scr->x1[rb][12 * mem + 6 * (grp & 1) + tid][0], 0, 0, 0, 0);
#pragma unroll 1
                for (int i = tid; i < 576; i += 256) {
                    const int kq = i / 36;
                    u64* pp = &scr->p1[mem][kq][grp][i - 36 * kq];
                    ll_st(pp, 0, 0); ll_st(pp + P2_MINUS_P1, 0, 0);
                }
            }
            const uint32_t kt = sb + slot * SLOT + offK;
            mbar_wait(bars + 8 * (BAR_FULL + slot), use & 1);
            float sa[4] = {0.f, 0.f, 0.f, 0.f}, sc2[4] = {0.f, 0.f, 0.f, 0.f};
#pragma unroll
            for (int ks = 0; ks < 8; ks++) {
                uint32_t a[4];
                ldsm4(a, kt + (ks >> 2) * 8192 + (xK ^ ((ks & 3) << 5)));
                if (ks & 1) mma16816(sc2, a, qf[2 * ks], qf[2 * ks + 1]); else mma16816(sa, a, qf[2 * ks], qf[2 * ks + 1]);
            }
            __syncwarp();
            if (lane == 0) mbar_arrive(bars + 8 * (BAR_EMPTY + slot));
            const uint32_t r01 = pack_bf16(sa[0] + sc2[0], sa[1] + sc2[1]), r23 = pack_bf16(sa[2] + sc2[2], sa[3] + sc2[3]);
            const float RS = 0.08838834764831845f;
            const uint32_t u01 = pack_bf16(bf_lo(r01) * RS, bf_hi(r01) * RS), u23 = pack_bf16(bf_lo(r23) * RS, bf_hi(r23) * RS);
            const float s0 = bf_lo(u01), s1 = bf_hi(u01), s2 = bf_lo(u23), s3 = bf_hi(u23);
            const bool grow = (s0 > m0) || (s2 > m0) || (s1 > m1) || (s3 > m1);
            if (__any_sync(0xffffffffu, grow)) {
                float n0 = fmaxf(s0, s2), n1 = fmaxf(s1, s3);
#pragma unroll
                for (int o = 4; o < 32; o <<= 1) {
                    n0 = fmaxf(n0, __shfl_xor_sync(0xffffffffu, n0, o));
                    n1 = fmaxf(n1, __shfl_xor_sync(0xffffffffu, n1, o));
                }
                n0 = fmaxf(n0, m0); n1 = fmaxf(n1, m1);
                const float a0 = ex2((m0 - n0) * SC), a1 = ex2((m1 - n1) * SC);
                m0 = n0; m1 = n1; l0 *= a0; l1 *= a1;
#pragma unroll
                for (int m = 0; m < 8; m++) { oacc[m][0] *= a0; oacc[m][1] *= a1; oacc[m][2] *= a0; oacc[m][3] *= a1; }
            }
            const float mc0 = m0 * SC, mc1 = m1 * SC;
            const float p0 = ex2(fmaf(s0, SC, -mc0)), p1 = ex2(fmaf(s1, SC, -mc1));
            const float p2 = ex2(fmaf(s2, SC, -mc0)), p3 = ex2(fmaf(s3, SC, -mc1));
            l0 += p0 + p2; l1 += p1 + p3;
            const uint32_t pb0 = movmat(pack_bf16(p0, p1)), pb1 = movmat(pack_bf16(p2, p3));
            const uint32_t vt = sb + (slot + 1) * SLOT + offV;
            mbar_wait(bars + 8 * (BAR_FULL + slot + 1), use & 1);
#pragma unroll
            for (int mt = 0; mt < 8; mt++) {
                uint32_t a[4];
                ldsm4t(a, vt + (mt >> 2) * 8192 + (xV ^ ((mt & 3) << 5)));
                mma16816(oacc[mt], a, pb0, pb1);
            }
            __syncwarp();
            if (lane == 0) mbar_arrive(bars + 8 * (BAR_EMPTY + slot + 1));
            slot += 4;
            if (slot >= NSLOT) { slot -= NSLOT; use++; }
        }
    }

    {
#pragma unroll
        for (int o = 4; o < 32; o <<= 1) { l0 += __shfl_xor_sync(0xffffffffu, l0, o); l1 += __shfl_xor_sync(0xffffffffu, l1, o); }
        const uint32_t ro = red + warp * 1024 + g * 8;
#pragma unroll
        for (int mt = 0; mt < 8; mt++) {
            if (t == (mt >> 1)) {
                sts64f(ro + mt * 128, oacc[mt][0], oacc[mt][1]);
                sts64f(ro + mt * 128 + 64, oacc[mt][2], oacc[mt][3]);
            }
        }
        if (lane == 0) sts128f(red + 8192 + warp * 16, m0, m1, l0, l1);
        u64* po = &scr->o[grp][mem][tid & 127];
        uint32_t rv = red + (tid & 63) * 16;
        PIN64(po); PIN32(rv);
        cbar();
        if (tid < 128) {
            const bool h = tid >= 64;
            float mw[8], lw[8], v0[8], v1[8];
#pragma unroll
            for (int w = 0; w < 8; w++) {
                const float4 a = lds128f(red + 8192 + w * 16), v = lds128f(rv + w * 1024);
                mw[w] = h ? a.y : a.x; lw[w] = h ? a.w : a.z;
                v0[w] = h ? v.y : v.x; v1[w] = h ? v.w : v.z;
            }
            const float M = fmaxf(fmaxf(fmaxf(mw[0], mw[1]), fmaxf(mw[2], mw[3])), fmaxf(fmaxf(mw[4], mw[5]), fmaxf(mw[6], mw[7])));
            float L = 0.f, o0 = 0.f, o1 = 0.f;
#pragma unroll
            for (int w = 0; w < 8; w++) {
                const float f = ex2((mw[w] - M) * SC);
                L = fmaf(f, lw[w], L); o0 = fmaf(f, v0[w], o0); o1 = fmaf(f, v1[w], o1);
            }
            const float inv = __fdividef(1.f, L);
            ll_st(po, pack_bf16(o0 * inv, o1 * inv), tag);
        }
    }
    const int rl = (lane & 7) + ((lane >> 4) << 3);
    const uint32_t a72 = sb + rl * 144 + (2 * warp + ((lane >> 3) & 1)) * 16;
    u64 *pw0, *pw1;
    {
        const int c0 = min(16 * warp + g, 71), c1 = min(16 * warp + g + 8, 71);
        u64* pb = &scr->p1[mem][4 * t][grp][0];
        pw0 = pb + (c0 >= 36 ? 576 + c0 - 36 : c0);
        pw1 = pb + (c1 >= 36 ? 576 + c1 - 36 : c1);
    }
    const bool hi_ok = warp < 4;
    {
        uint32_t wa[16][4];
        mbar_wait(bars + 8 * (BAR_T + 0), 0);
        mbar_wait(bars + 8 * (BAR_T + 1), 0);
        gemv72_load<16>(wa, a72 + T_WO);
        const u64* po = &scr->o[grp][warp][lane];
        uint32_t dst = actb + warp * ACTB_O_PITCH + lane * 4;
        uint32_t baddr = actb + (lane & 7) * ACTB_O_PITCH + (lane >> 3) * 16;
        PIN64(pw0); PIN64(pw1); PIN32(dst); PIN32(baddr);
        uint32_t ov[4];
        ll_poll<4, 32>(po, tag, ov);
#pragma unroll
        for (int k = 0; k < 4; k++) sts32(dst + 128 * k, ov[k]);
        cbar();
        if (warp < 5) gemv72_run<16>(wa, baddr, pw0, pw1, hi_ok, tag);
    }
    uint32_t x1_r = 0;
    const u64* pr = &scr->p1[mem][grp][2 * warp][lane < 18 ? 2 * lane : 0];
    {
        u64* px = &scr->x1[rb][12 * mem + 6 * (grp & 1) + (lane < 6 ? lane : 0)][0];
        int src = lane < 6 ? 3 * lane : 0;
        PIN64(px); PIN32(src);
        float a0 = 0.f, a1 = 0.f;
        reduce16(pr, red, warp, lane, tag, a0, a1);
        if (warp == 7) {
            x1_r = pack_bf16(fmaf(bf_lo(ga_r), a0, bf_lo(x_r)), fmaf(bf_hi(ga_r), a1, bf_hi(x_r)));
            const uint32_t w0 = __shfl_sync(0xffffffffu, x1_r, src), w1 = __shfl_sync(0xffffffffu, x1_r, src + 1),
                           w2 = __shfl_sync(0xffffffffu, x1_r, src + 2);
            if (lane < 6) ll_st128(px, w0, w1, w2, tag);
        }
    }
    {
        const int mat = warp >> 2, kg = warp & 3;
#pragma unroll 1
        for (int p = 0; p < 3; p++) mbar_wait(bars + 8 * (BAR_T + 2 + 3 * mat + p), 0);
        const uint32_t aaddr = sb + (mat ? T_WU : T_WG) + (144 * kg + rl) * 80 + ((lane >> 3) & 1) * 16;
        uint32_t wa[9][3][4];
#pragma unroll
        for (int i = 0; i < 6; i++)
#pragma unroll
            for (int m = 0; m < 3; m++) ldsm4t(wa[i][m], aaddr + i * 16 * 80 + m * 32);

        const u64* xp = &scr->x1[warp][lane][0];
        uint32_t adst = act_row + 12 * lane;
        uint32_t baddr = act + (lane & 7) * ACT_PITCH + (lane >> 3) * 16 + 288 * kg;
        PIN32(adst); PIN32(baddr);
        asm volatile("bar.sync 4, 256;" ::: "memory");
        uint32_t xv[9];
        {
            int it = 0;
            uint32_t bad;
            do {
                bad = 0;
#pragma unroll
                for (int k = 0; k < 3; k++) {
                    uint32_t tg;
                    ll_ld128(xp + 64 * k, xv[3 * k], xv[3 * k + 1], xv[3 * k + 2], tg);
                    bad |= tg ^ tag;
                }
            } while (!poll_done(bad, it));
        }
        float mean, den;
        ln_stats<true>(xv, mean, den);
        const uint32_t m2 = pack_bf16(mean, mean);
        float rinv;
        asm("rcp.approx.f32 %0, %1;" : "=f"(rinv) : "f"(den));
#pragma unroll
        for (int k = 0; k < 9; k++) sts32(adst + 384 * (k / 3) + 4 * (k % 3), ln_mod2(xv[k], m2, rinv, cbv[k], sbv[k]));
#pragma unroll
        for (int i = 6; i < 9; i++)
#pragma unroll
            for (int m = 0; m < 3; m++) ldsm4t(wa[i][m], aaddr + i * 16 * 80 + m * 32);
        uint32_t rdst = red + warp * 1536 + g * 32 + t * 8;
        uint32_t rsrc = red + (((36 * cta) & 7) + 2 * (tid >> 3)) * 32 + (tid & 7) * 4;
        u64* ph = &scr->hh[grp][18 * mem][0] + (tid < 144 ? tid : 0);
        PIN32(rdst); PIN32(rsrc); PIN64(ph);
        cbar();
        float c[2][3][4];
#pragma unroll
        for (int m = 0; m < 3; m++)
#pragma unroll
            for (int j = 0; j < 4; j++) c[0][m][j] = c[1][m][j] = 0.f;
#pragma unroll
        for (int i = 0; i < 9; i += 2) {
            uint32_t b[4];
            ldsm4(b, baddr + i * 32);
#pragma unroll
            for (int m = 0; m < 3; m++) {
                mma16816(c[0][m], wa[i][m], b[0], b[1]);
                if (i + 1 < 9) mma16816(c[1][m], wa[i + 1][m], b[2], b[3]);
            }
        }
#pragma unroll
        for (int m = 0; m < 3; m++) {
            sts64f(rdst + m * 512, c[0][m][0] + c[1][m][0], c[0][m][1] + c[1][m][1]);
            sts64f(rdst + m * 512 + 256, c[0][m][2] + c[1][m][2], c[0][m][3] + c[1][m][3]);
        }
        cbar();
        if (tid < 144) {
            float r[2];
#pragma unroll
            for (int e = 0; e < 2; e++) {
                const uint32_t a = rsrc + 32 * e;
                const float gg = (ldsf(a) + ldsf(a + 1536)) + (ldsf(a + 3072) + ldsf(a + 4608));
                const float uu = (ldsf(a + 6144) + ldsf(a + 7680)) + (ldsf(a + 9216) + ldsf(a + 10752));
                r[e] = gelu_f(gg) * uu;
            }
            ll_st(ph, pack_bf16(r[0], r[1]), tag);
        }
        if (cta == 0 && tid == 255) {
            asm volatile("st.relaxed.gpu.global.u32 [%0], %1;" ::"l"(&scr->epoch), "r"(tag) : "memory");
            asm volatile("st.relaxed.gpu.global.u32 [%0], %1;" ::"l"(&scr->prog), "r"(0u) : "memory");
        }
    }
    {
        uint32_t wa[18][4];
#pragma unroll 1
        for (int p = 0; p < 3; p++) mbar_wait(bars + 8 * (BAR_T + 8 + p), 0);
        gemv72_load<18>(wa, a72 + T_WD);
        const u64* hp = &scr->hh[grp][0][0] + tid;
        const u64* hl = &scr->hh[grp][128][0] + (tid & 127);
        uint32_t dst = actb + (tid & 7) * ACTB_H_PITCH + (tid >> 3) * 4;
        uint32_t dl = actb + (tid & 7) * ACTB_H_PITCH + (128 + ((tid & 127) >> 3)) * 4;
        uint32_t baddr = actb + (lane & 7) * ACTB_H_PITCH + (lane >> 3) * 16;
        u64 *q0 = pw0 + P2_MINUS_P1, *q1 = pw1 + P2_MINUS_P1;
        PIN32(dst); PIN32(dl); PIN32(baddr); PIN64(q0); PIN64(q1);
        uint32_t hv[5];
        {
            int it = 0;
            uint32_t bad;
            do {
                bad = 0;
#pragma unroll
                for (int k = 0; k < 5; k++) { uint32_t tg; ll_ld(k < 4 ? hp + 256 * k : hl, hv[k], tg); bad |= tg ^ tag; }
            } while (!poll_done(bad, it));
        }
#pragma unroll
        for (int k = 0; k < 4; k++) sts32(dst + 128 * k, hv[k]);
        sts32(dl, hv[4]);
        cbar();
        if (warp < 5) gemv72_run<18>(wa, baddr, q0, q1, hi_ok, tag);
    }
    {
        uint32_t* po = reinterpret_cast<uint32_t*>(prm.out + rb * DM) + rpair;
        PIN64(po);
        float a0 = 0.f, a1 = 0.f;
        reduce16(pr + P2_MINUS_P1, red, warp, lane, tag, a0, a1);
        if (warp == 7) {
            if (lane < 18) *po = pack_bf16(fmaf(bf_lo(gb_r), a0, bf_lo(x1_r)), fmaf(bf_hi(gb_r), a1, bf_hi(x1_r)));
        }
    }
}

typedef CUresult (*EncodeFn)(CUtensorMap*, CUtensorMapDataType, cuuint32_t, void*, const cuuint64_t*, const cuuint64_t*,
                             const cuuint32_t*, const cuuint32_t*, CUtensorMapInterleave, CUtensorMapSwizzle,
                             CUtensorMapL2promotion, CUtensorMapFloatOOBfill);

void make_map2d(EncodeFn enc, CUtensorMap* m, const void* ptr, uint64_t cols, uint64_t rows, uint32_t bc, uint32_t br,
                CUtensorMapSwizzle sw, CUtensorMapL2promotion pr) {
    cuuint64_t dims[2] = {cols, rows};
    cuuint64_t strides[1] = {cols * 2};
    cuuint32_t box[2] = {bc, br};
    cuuint32_t es[2] = {1, 1};
    enc(m, CU_TENSOR_MAP_DATA_TYPE_BFLOAT16, 2, const_cast<void*>(ptr), dims, strides, box, es,
        CU_TENSOR_MAP_INTERLEAVE_NONE, sw, pr, CU_TENSOR_MAP_FLOAT_OOB_FILL_NONE);
}
void make_map_kv(EncodeFn enc, CUtensorMap* m, const void* ptr) {
    cuuint64_t dims[3] = {64, (cuuint64_t)NB * 16 * SK, 2};
    cuuint64_t strides[2] = {256, 128};
    cuuint32_t box[3] = {64, 64, 2};
    cuuint32_t es[3] = {1, 1, 1};
    enc(m, CU_TENSOR_MAP_DATA_TYPE_BFLOAT16, 3, const_cast<void*>(ptr), dims, strides, box, es,
        CU_TENSOR_MAP_INTERLEAVE_NONE, CU_TENSOR_MAP_SWIZZLE_128B, CU_TENSOR_MAP_L2_PROMOTION_L2_256B,
        CU_TENSOR_MAP_FLOAT_OOB_FILL_NONE);
}

}

extern "C" void kernel_launch(void* const* d_in, const int* in_sizes, int n_in, void* d_out, int out_size) {
    (void)in_sizes; (void)n_in; (void)out_size;
    static EncodeFn enc = nullptr;
    static Scratch* scr = nullptr;
    if (!enc) {
        void* fn = nullptr;
        cudaDriverEntryPointQueryResult qr;
        cudaGetDriverEntryPoint("cuTensorMapEncodeTiled", &fn, cudaEnableDefault, &qr);
        enc = (EncodeFn)fn;
        cudaGetSymbolAddress((void**)&scr, g_scr);
        cudaFuncSetAttribute(adaln_gqa_geglu_decode_kernel, cudaFuncAttributeMaxDynamicSharedMemorySize, SMEM_BYTES);
    }
    CUtensorMap tmK, tmV, tmMod, tmWq, tmWo, tmWg, tmWu, tmWd;
    make_map_kv(enc, &tmK, d_in[1]);
    make_map_kv(enc, &tmV, d_in[2]);
    make_map2d(enc, &tmMod, d_in[10], 6 * DM, DM, 32, 192, CU_TENSOR_MAP_SWIZZLE_64B, CU_TENSOR_MAP_L2_PROMOTION_L2_128B);
    make_map2d(enc, &tmWq, d_in[3], 4096, DM, 32, 192, CU_TENSOR_MAP_SWIZZLE_64B, CU_TENSOR_MAP_L2_PROMOTION_L2_128B);
    make_map2d(enc, &tmWo, d_in[4], DM, 4096, 72, 128, CU_TENSOR_MAP_SWIZZLE_NONE, CU_TENSOR_MAP_L2_PROMOTION_L2_128B);
    make_map2d(enc, &tmWg, d_in[6], DF, DM, 40, 192, CU_TENSOR_MAP_SWIZZLE_NONE, CU_TENSOR_MAP_L2_PROMOTION_L2_128B);
    make_map2d(enc, &tmWu, d_in[7], DF, DM, 40, 192, CU_TENSOR_MAP_SWIZZLE_NONE, CU_TENSOR_MAP_L2_PROMOTION_L2_128B);
    make_map2d(enc, &tmWd, d_in[8], DM, DF, 72, 96, CU_TENSOR_MAP_SWIZZLE_NONE, CU_TENSOR_MAP_L2_PROMOTION_L2_128B);
    Params prm;
    prm.x = (const __nv_bfloat16*)d_in[0];
    prm.c = (const __nv_bfloat16*)d_in[9];
    prm.wmod = (const __nv_bfloat16*)d_in[10];
    prm.out = (__nv_bfloat16*)d_out;
    prm.scr = scr;
    adaln_gqa_geglu_decode_kernel<<<NCTA + NXTRA, NTHREADS, SMEM_BYTES, cudaStreamPerThread>>>(prm, tmK, tmV, tmMod, tmWq, tmWo, tmWg, tmWu, tmWd);
}
```

```cpp
#include <cuda_runtime.h>
#include <cuda_bf16.h>
#include <cuda.h>
#include <stdint.h>
#include <stddef.h>

namespace {

typedef unsigned long long u64;

constexpr int NB = 8;
constexpr int DM = 576;
constexpr int SK = 8192;
constexpr int DF = 4608;
constexpr int NCTA = 128;
constexpr int NXTRA = 4;
constexpr int NTHREADS = 288;

constexpr int NSLOT = 12;
constexpr int SLOT = 16384;
constexpr int RING = NSLOT * SLOT;
constexpr int P_REG = DM * 64;
constexpr int P_A = 3 * SLOT;
constexpr int P_B = P_A + P_REG;
constexpr int T_WO = 0;
constexpr int T_WG = T_WO + 256 * 144;
constexpr int T_WU = T_WG + DM * 80;
constexpr int T_WD = T_WU + DM * 80;
constexpr int T_END = T_WD + 288 * 144;
static_assert(T_END <= RING, "tail overlay");
static_assert(P_B + P_REG <= 8 * SLOT, "prologue overlay");
constexpr int ACT_PITCH = 1168;
constexpr int OFF_ACT = RING;
constexpr int OFF_RED = OFF_ACT + NB * ACT_PITCH;
constexpr int RED_BYTES = 12288 + 256;
constexpr int ACTB_O_PITCH = 528;
constexpr int ACTB_H_PITCH = 592;
constexpr int OFF_ACTB = OFF_RED + RED_BYTES;
constexpr int OFF_STAT = OFF_ACTB + NB * ACTB_H_PITCH;
constexpr int OFF_BAR = OFF_STAT + 128;
constexpr int BAR_FULL = 0, BAR_EMPTY = NSLOT, BAR_P = 2 * NSLOT, BAR_T = BAR_P + 6;
constexpr int NT_PIECES = 11;
constexpr int NBARS = BAR_T + NT_PIECES;
constexpr int OFF_Q = OFF_BAR + NBARS * 8;
constexpr int SMEM_USED = OFF_Q + 16 * 8;
constexpr int SMEM_BYTES = SMEM_USED + 1024;
static_assert(SMEM_BYTES <= 232448, "smem");

constexpr int NTILES = 256;
constexpr int TILE0 = 8;
constexpr int TILE_END = TILE0 + NTILES;
constexpr int LAST_USE = (TILE_END - 1) / NSLOT;
static_assert(TILE_END % NSLOT == 0, "last round must end with the last slot");

#define PACE_D0 4
#define PACE_GAIN 6
#define PACE_BIAS 0
#define PACE_DMIN 1
#define PACE_DMAX 8
#define PACE_DSTART 3
#define MID_KB 64
#define START_TILES 2
#define WIN_T 40000

constexpr int SPIN_LIMIT = 1 << 21;

struct Scratch {
    u64 h0[NB][128][2];
    u64 mod[NB][1152];
    u64 q[16][NB][128];
    u64 o[16][NB][128];
    u64 p1[8][16][16][36];
    u64 x1[NB][96][2];
    u64 hh[16][144][NB];
    u64 p2[8][16][16][36];
    unsigned int epoch, pad0[31];
    unsigned int prog, pad1[31];
};
__device__ __align__(1024) Scratch g_scr;
constexpr int P2_MINUS_P1 = (int)((offsetof(Scratch, p2) - offsetof(Scratch, p1)) / 8);

#define PIN32(x) asm volatile("" : "+r"(x))
#define PIN64(x) asm volatile("" : "+l"(x))

__device__ __forceinline__ uint32_t smem_u32(const void* p) { return (uint32_t)__cvta_generic_to_shared(p); }
__device__ __forceinline__ void sts32(uint32_t a, uint32_t v) { asm volatile("st.shared.b32 [%0], %1;" ::"r"(a), "r"(v) : "memory"); }
__device__ __forceinline__ void sts64f(uint32_t a, float x, float y) { asm volatile("st.shared.v2.f32 [%0], {%1, %2};" ::"r"(a), "f"(x), "f"(y) : "memory"); }
__device__ __forceinline__ void sts128f(uint32_t a, float x, float y, float z, float w) {
    asm volatile("st.shared.v4.f32 [%0], {%1, %2, %3, %4};" ::"r"(a), "f"(x), "f"(y), "f"(z), "f"(w) : "memory");
}
__device__ __forceinline__ uint32_t lds32(uint32_t a) { uint32_t v; asm volatile("ld.shared.b32 %0, [%1];" : "=r"(v) : "r"(a)); return v; }
__device__ __forceinline__ float ldsf(uint32_t a) { float v; asm volatile("ld.shared.f32 %0, [%1];" : "=f"(v) : "r"(a)); return v; }
__device__ __forceinline__ float4 lds128f(uint32_t a) {
    float4 v;
    asm volatile("ld.shared.v4.f32 {%0, %1, %2, %3}, [%4];" : "=f"(v.x), "=f"(v.y), "=f"(v.z), "=f"(v.w) : "r"(a));
    return v;
}

__device__ __forceinline__ void mbar_init(uint32_t bar, uint32_t cnt) {
    asm volatile("mbarrier.init.shared::cta.b64 [%0], %1;" ::"r"(bar), "r"(cnt) : "memory");
}
__device__ __forceinline__ void mbar_expect_tx(uint32_t bar, uint32_t bytes) {
    asm volatile("mbarrier.arrive.expect_tx.shared::cta.b64 _, [%0], %1;" ::"r"(bar), "r"(bytes) : "memory");
}
__device__ __forceinline__ void mbar_arrive(uint32_t bar) {
    asm volatile("mbarrier.arrive.shared::cta.b64 _, [%0];" ::"r"(bar) : "memory");
}
__device__ __forceinline__ void mbar_arrive_n(uint32_t bar, uint32_t n) {
    asm volatile("mbarrier.arrive.shared::cta.b64 _, [%0], %1;" ::"r"(bar), "r"(n) : "memory");
}
__device__ __forceinline__ void mbar_wait(uint32_t bar, uint32_t parity) {
    asm volatile(
        "{\n.reg .pred p;\n.reg .u32 n;\nmov.u32 n, 0;\n"
        "W: mbarrier.try_wait.parity.shared::cta.b64 p, [%0], %1;\n"
        "@p bra D;\nadd.u32 n, n, 1;\nsetp.lt.u32 p, n, %2;\n@p bra W;\ntrap;\nD:\n}"
        ::"r"(bar), "r"(parity), "n"(SPIN_LIMIT) : "memory");
}
__device__ __forceinline__ void cbar() { asm volatile("bar.sync 1, 256;" ::: "memory"); }

__device__ __forceinline__ void tma2d(uint32_t dst, const CUtensorMap* tm, int c0, int c1, uint32_t bar) {
    asm volatile("cp.async.bulk.tensor.2d.shared::cluster.global.mbarrier::complete_tx::bytes [%0], [%1, {%3, %4}], [%2];"
                 ::"r"(dst), "l"(tm), "r"(bar), "r"(c0), "r"(c1) : "memory");
}
__device__ __forceinline__ void tma3d_hint(uint32_t dst, const CUtensorMap* tm, int c0, int c1, int c2, uint32_t bar, uint64_t pol) {
    asm volatile("cp.async.bulk.tensor.3d.shared::cluster.global.mbarrier::complete_tx::bytes.L2::cache_hint [%0], [%1, {%3, %4, %5}], [%2], %6;"
                 ::"r"(dst), "l"(tm), "r"(bar), "r"(c0), "r"(c1), "r"(c2), "l"(pol) : "memory");
}
__device__ __forceinline__ void ldsm4(uint32_t (&r)[4], uint32_t a) {
    asm volatile("ldmatrix.sync.aligned.m8n8.x4.shared.b16 {%0,%1,%2,%3}, [%4];"
                 : "=r"(r[0]), "=r"(r[1]), "=r"(r[2]), "=r"(r[3]) : "r"(a));
}
__device__ __forceinline__ void ldsm4t(uint32_t (&r)[4], uint32_t a) {
    asm volatile("ldmatrix.sync.aligned.m8n8.x4.trans.shared.b16 {%0,%1,%2,%3}, [%4];"
                 : "=r"(r[0]), "=r"(r[1]), "=r"(r[2]), "=r"(r[3]) : "r"(a));
}
__device__ __forceinline__ void ldsm2(uint32_t& r0, uint32_t& r1, uint32_t a) {
    asm volatile("ldmatrix.sync.aligned.m8n8.x2.shared.b16 {%0,%1}, [%2];" : "=r"(r0), "=r"(r1) : "r"(a));
}
__device__ __forceinline__ void mma16816(float (&c)[4], const uint32_t (&a)[4], uint32_t b0, uint32_t b1) {
    asm volatile("mma.sync.aligned.m16n8k16.row.col.f32.bf16.bf16.f32 {%0,%1,%2,%3}, {%4,%5,%6,%7}, {%8,%9}, {%0,%1,%2,%3};"
                 : "+f"(c[0]), "+f"(c[1]), "+f"(c[2]), "+f"(c[3])
                 : "r"(a[0]), "r"(a[1]), "r"(a[2]), "r"(a[3]), "r"(b0), "r"(b1));
}
__device__ __forceinline__ uint32_t movmat(uint32_t a) {
    uint32_t d;
    asm volatile("movmatrix.sync.aligned.m8n8.trans.b16 %0, %1;" : "=r"(d) : "r"(a));
    return d;
}
__device__ __forceinline__ float ex2(float x) {
    float y;
    asm("ex2.approx.ftz.f32 %0, %1;" : "=f"(y) : "f"(x));
    return y;
}
__device__ __forceinline__ uint32_t pack_bf16(float lo, float hi) {
    __nv_bfloat162 v = __floats2bfloat162_rn(lo, hi);
    return *reinterpret_cast<uint32_t*>(&v);
}
__device__ __forceinline__ float bf_lo(uint32_t v) { return __uint_as_float(v << 16); }
__device__ __forceinline__ float bf_hi(uint32_t v) { return __uint_as_float(v & 0xffff0000u); }
__device__ __forceinline__ float rbf(float x) { return __bfloat162float(__float2bfloat16_rn(x)); }

__device__ __forceinline__ void ll_st(u64* p, uint32_t data, uint32_t tag) {
    asm volatile("{\n.reg .b64 v;\nmov.b64 v, {%1, %2};\nst.relaxed.gpu.global.b64 [%0], v;\n}" ::"l"(p), "r"(data), "r"(tag) : "memory");
}
__device__ __forceinline__ void ll_ld(const u64* p, uint32_t& data, uint32_t& tg) {
    asm volatile("{\n.reg .b64 v;\nld.relaxed.gpu.global.b64 v, [%2];\nmov.b64 {%0, %1}, v;\n}" : "=r"(data), "=r"(tg) : "l"(p) : "memory");
}
__device__ __forceinline__ void ll_ld2(const u64* p, uint32_t& d0, uint32_t& t0, uint32_t& d1, uint32_t& t1) {
    asm volatile("{\n.reg .b64 a, b;\nld.relaxed.gpu.global.v2.b64 {a, b}, [%4];\nmov.b64 {%0, %1}, a;\nmov.b64 {%2, %3}, b;\n}"
                 : "=r"(d0), "=r"(t0), "=r"(d1), "=r"(t1) : "l"(p) : "memory");
}
__device__ __forceinline__ void ll_st128(u64* p, uint32_t w0, uint32_t w1, uint32_t w2, uint32_t tag) {
    asm volatile("{\n.reg .b128 r;\n.reg .b64 lo, hi;\nmov.b64 lo, {%1, %2};\nmov.b64 hi, {%3, %4};\nmov.b128 r, {lo, hi};\n"
                 "st.relaxed.gpu.global.b128 [%0], r;\n}" ::"l"(p), "r"(w0), "r"(w1), "r"(w2), "r"(tag) : "memory");
}
__device__ __forceinline__ void ll_ld128(const u64* p, uint32_t& w0, uint32_t& w1, uint32_t& w2, uint32_t& tg) {
    asm volatile("{\n.reg .b128 r;\n.reg .b64 lo, hi;\nld.relaxed.gpu.global.b128 r, [%4];\nmov.b128 {lo, hi}, r;\n"
                 "mov.b64 {%0, %1}, lo;\nmov.b64 {%2, %3}, hi;\n}" : "=r"(w0), "=r"(w1), "=r"(w2), "=r"(tg) : "l"(p) : "memory");
}
__device__ __forceinline__ bool poll_done(uint32_t bad, int& it) {
    if (!__any_sync(0xffffffffu, bad != 0)) return true;
    if (++it > SPIN_LIMIT) __trap();
    return false;
}
template <int N, int STRIDE>
__device__ __forceinline__ void ll_poll(const u64* p, uint32_t tag, uint32_t (&out)[N]) {
    int it = 0;
    uint32_t bad;
    do {
        bad = 0;
#pragma unroll
        for (int i = 0; i < N; i++) { uint32_t tg; ll_ld(p + i * STRIDE, out[i], tg); bad |= tg ^ tag; }
    } while (!poll_done(bad, it));
}
__device__ __forceinline__ void reduce16(const u64* p, uint32_t buf, int warp, int lane, uint32_t tag, float& s0, float& s1) {
    uint32_t a0, a1, b0, b1;
    {
        int it = 0;
        uint32_t bad;
        do {
            uint32_t t0, t1, t2, t3;
            ll_ld2(p, a0, t0, a1, t1);
            ll_ld2(p + 36, b0, t2, b1, t3);
            bad = ((t0 ^ tag) | (t1 ^ tag)) | ((t2 ^ tag) | (t3 ^ tag));
        } while (!poll_done(bad, it));
    }
    if (lane < 18) sts64f(buf + (warp * 18 + lane) * 8, __uint_as_float(a0) + __uint_as_float(b0), __uint_as_float(a1) + __uint_as_float(b1));
    if (warp != 7) {
        asm volatile("bar.arrive 3, 256;" ::: "memory");
    } else {
        asm volatile("bar.sync 3, 256;" ::: "memory");
        float x[8], y[8];
        const uint32_t q = buf + (lane < 18 ? lane : 0) * 8;
#pragma unroll
        for (int w = 0; w < 8; w++) asm volatile("ld.shared.v2.f32 {%0, %1}, [%2];" : "=f"(x[w]), "=f"(y[w]) : "r"(q + w * 144));
        s0 = ((x[0] + x[1]) + (x[2] + x[3])) + ((x[4] + x[5]) + (x[6] + x[7]));
        s1 = ((y[0] + y[1]) + (y[2] + y[3])) + ((y[4] + y[5]) + (y[6] + y[7]));
    }
}

template <bool FAST>
__device__ __forceinline__ void ln_stats(const uint32_t (&v)[9], float& mean, float& den) {
    const float k = __shfl_sync(0xffffffffu, bf_lo(v[0]), 0);
    float s = 0.f, q = 0.f;
#pragma unroll
    for (int i = 0; i < 9; i++) {
        const float a = bf_lo(v[i]) - k, b = bf_hi(v[i]) - k;
        s += a + b;
        q = fmaf(a, a, fmaf(b, b, q));
    }
#pragma unroll
    for (int o = 16; o > 0; o >>= 1) { s += __shfl_xor_sync(0xffffffffu, s, o); q += __shfl_xor_sync(0xffffffffu, q, o); }
    const float md = s * (1.0f / DM);
    mean = rbf(k + md);
    const float ve = rbf(rbf(fmaxf(q * (1.0f / DM) - md * md, 0.f)) + 1e-5f);
    float r;
    if (FAST) asm("sqrt.approx.f32 %0, %1;" : "=f"(r) : "f"(ve)); else r = __fsqrt_rn(ve);
    den = rbf(r);
}
__device__ __forceinline__ uint32_t bf2_add(uint32_t a, uint32_t b) {
    uint32_t d; asm("add.rn.bf16x2 %0, %1, %2;" : "=r"(d) : "r"(a), "r"(b)); return d;
}
__device__ __forceinline__ uint32_t bf2_sub(uint32_t a, uint32_t b) {
    uint32_t d; asm("sub.rn.bf16x2 %0, %1, %2;" : "=r"(d) : "r"(a), "r"(b)); return d;
}
__device__ __forceinline__ uint32_t bf2_mul(uint32_t a, uint32_t b) {
    uint32_t d; asm("mul.rn.bf16x2 %0, %1, %2;" : "=r"(d) : "r"(a), "r"(b)); return d;
}
__device__ __forceinline__ uint32_t ln_mod2(uint32_t x, uint32_t m2, float rinv, uint32_t c1, uint32_t sh) {
    const uint32_t d = bf2_sub(x, m2);
    const uint32_t n = pack_bf16(bf_lo(d) * rinv, bf_hi(d) * rinv);
    return bf2_add(bf2_mul(n, c1), sh);
}
constexpr uint32_t BF2_ONE = 0x3f803f80u;
__device__ __forceinline__ float silu_f(float a) { return __fdividef(a, 1.f + __expf(-a)); }
__device__ __forceinline__ float gelu_f(float g) {
    const float z2 = 1.5957691216057308f * fmaf(0.044715f * g * g, g, g);
    return __fdividef(g, 1.f + __expf(-z2));
}

template <int KSTEPS>
__device__ __forceinline__ void gemv72_load(uint32_t (&a)[KSTEPS][4], uint32_t aaddr) {
#pragma unroll
    for (int i = 0; i < KSTEPS; i++) ldsm4t(a[i], aaddr + i * 16 * 144);
}
template <int KSTEPS>
__device__ __forceinline__ void gemv72_run(const uint32_t (&a)[KSTEPS][4], uint32_t baddr, u64* p0, u64* p1, bool hi_ok, uint32_t tag) {
    float c[4][4];
#pragma unroll
    for (int j = 0; j < 4; j++) c[j][0] = c[j][1] = c[j][2] = c[j][3] = 0.f;
#pragma unroll
    for (int i = 0; i < KSTEPS; i += 2) {
        uint32_t b[4];
        ldsm4(b, baddr + i * 32);
        mma16816(c[i & 3], a[i], b[0], b[1]);
        mma16816(c[(i + 1) & 3], a[i + 1], b[2], b[3]);
    }
    const float r0 = (c[0][0] + c[1][0]) + (c[2][0] + c[3][0]), r1 = (c[0][1] + c[1][1]) + (c[2][1] + c[3][1]);
    const float r2 = (c[0][2] + c[1][2]) + (c[2][2] + c[3][2]), r3 = (c[0][3] + c[1][3]) + (c[2][3] + c[3][3]);
    ll_st(p0, __float_as_uint(r0), tag); ll_st(p0 + 2 * 576, __float_as_uint(r1), tag);
    if (hi_ok) { ll_st(p1, __float_as_uint(r2), tag); ll_st(p1 + 2 * 576, __float_as_uint(r3), tag); }
}

struct Params {
    const __nv_bfloat16* x;
    const __nv_bfloat16* c;
    const __nv_bfloat16* wmod;
    __nv_bfloat16* out;
    Scratch* scr;
};

__global__ void __launch_bounds__(NTHREADS, 1)
adaln_gqa_geglu_decode_kernel(const Params prm,
                              const __grid_constant__ CUtensorMap tmK, const __grid_constant__ CUtensorMap tmV,
                              const __grid_constant__ CUtensorMap tmMod, const __grid_constant__ CUtensorMap tmWq,
                              const __grid_constant__ CUtensorMap tmWo, const __grid_constant__ CUtensorMap tmWg,
                              const __grid_constant__ CUtensorMap tmWu, const __grid_constant__ CUtensorMap tmWd) {
    extern __shared__ unsigned char smem_raw[];
    uint32_t sb = (smem_u32(smem_raw) + 1023u) & ~1023u;
    int tid = threadIdx.x, cta = blockIdx.x;
    Scratch* scr = prm.scr;
    PIN32(sb); PIN32(tid); PIN32(cta); PIN64(scr);
    const uint32_t bars = sb + OFF_BAR;
    const int warp = tid >> 5, lane = tid & 31;
    const int grp = cta >> 3, mem = cta & 7;
    const bool extra = cta >= NCTA;

    if (warp == 8) {
        if (lane < 8) {
            const CUtensorMap* tm = lane == 0 ? &tmMod : lane == 1 ? &tmWq : lane == 2 ? &tmK : lane == 3 ? &tmV
                                  : lane == 4 ? &tmWo : lane == 5 ? &tmWg : lane == 6 ? &tmWu : &tmWd;
            asm volatile("prefetch.tensormap [%0];" ::"l"(tm) : "memory");
        }
        if (lane == 0) {
#pragma unroll
            for (int s = 0; s < NBARS; s++) mbar_init(bars + 8 * s, (s >= BAR_EMPTY && s < BAR_P) ? 4 : 1);
#pragma unroll
            for (int s = 0; s < 8; s++) {
                mbar_arrive(bars + 8 * (BAR_FULL + s));
                if (s < 3 || (s < 5 && cta >= 36)) mbar_arrive_n(bars + 8 * (BAR_EMPTY + s), 4);
            }
            asm volatile("fence.mbarrier_init.release.cluster;" ::: "memory");
        }
        __syncwarp();
        asm volatile("bar.arrive 2, 288;" ::: "memory");
        if (lane == 0 && !extra) {
            uint64_t pol;
            asm volatile("createpolicy.fractional.L2::evict_first.b64 %0, 1.0;" : "=l"(pol));
            const uint32_t fifo = sb + OFF_Q;
            const int row0 = (mem * 16 + grp) * SK;
            const int boxcol = (36 * cta) & ~7;
            int head = 0, tail = 0, inflight = 0;
            int pi = 0, tp = TILE0, ti = 0, freed = 0, slot = TILE0, use = 0, win = PACE_DSTART, own_at = 0;
            unsigned gpend = 0;
#pragma unroll 1
            while (true) {
                uint32_t bar, par = 0;
                int bytes, window, kind;
                if (pi < 3) {
                    kind = 0; bar = bars + 8 * (BAR_P + 3 + pi); bytes = 12288; window = 1 << 30;
                } else if (tp < TILE_END) {
                    kind = 1;
                    if (use > 0) mbar_wait(bars + 8 * (BAR_EMPTY + slot), (use - 1) & 1);
                    if (PACE_GAIN > 0 && (tp & 1) == 0) {
                        if (tp >= TILE0 + 12) {
                            const int sc = (own_at * NCTA - (int)gpend - PACE_BIAS) * PACE_GAIN;
                            const int adj = sc >= 0 ? (sc + 2 * NCTA) / (4 * NCTA) : -((-sc + 2 * NCTA) / (4 * NCTA));
                            win = min(max(PACE_D0 - adj, PACE_DMIN), PACE_DMAX);
                        }
                        asm volatile("red.relaxed.gpu.global.add.u32 [%0], 1;" ::"l"(&scr->prog) : "memory");
                        own_at = ((tp - TILE0) >> 1) + 1;
                        asm volatile("ld.relaxed.gpu.global.u32 %0, [%1];" : "=r"(gpend) : "l"(&scr->prog) : "memory");
                    } else if (PACE_GAIN == 0 && tp >= TILE0 + 12) win = PACE_D0;
                    bar = bars + 8 * (BAR_FULL + slot); par = use & 1; bytes = SLOT; window = tp < TILE0 + START_TILES ? (1 << 30) : win * SLOT;
                } else if (ti < NT_PIECES) {
                    kind = 2;
                    bytes = ti < 2 ? 18432 : ti < 8 ? 15360 : 13824;
                    const int end = ti < 2 ? 18432 * (ti + 1) : ti < 8 ? T_WG + 15360 * (ti - 1) : T_WD + 13824 * (ti - 7);
                    while (freed * SLOT < end) { mbar_wait(bars + 8 * (BAR_EMPTY + freed), LAST_USE & 1); freed++; }
                    bar = bars + 8 * (BAR_T + ti);
                    window = WIN_T;
                } else break;
                while (head != tail && inflight + bytes > window) {
                    const uint32_t e = lds32(fifo + 8 * (head & 15));
                    mbar_wait(e & ~1u, e & 1u);
                    inflight -= (int)lds32(fifo + 8 * (head & 15) + 4);
                    head++;
                }
                sts32(fifo + 8 * (tail & 15), bar | par); sts32(fifo + 8 * (tail & 15) + 4, bytes);
                tail++; inflight += bytes;
                mbar_expect_tx(bar, bytes);
                if (kind == 0) {
                    tma2d(sb + P_B + pi * 12288, &tmWq, 32 * cta, 192 * pi, bar);
                    pi++;
                } else if (kind == 1) {
                    tma3d_hint(sb + slot * SLOT, (tp & 1) ? &tmV : &tmK, 0, row0 + ((tp - TILE0) >> 1) * 64, 0, bar, pol);
                    if (++slot == NSLOT) { slot = 0; use++; }
                    tp++;
                } else {
                    const CUtensorMap* tm = ti < 2 ? &tmWo : ti < 5 ? &tmWg : ti < 8 ? &tmWu : &tmWd;
                    const int off = ti < 2 ? 18432 * ti : ti < 8 ? T_WG + 15360 * (ti - 2) : T_WD + 13824 * (ti - 8);
                    const int c0 = (ti >= 2 && ti < 8) ? boxcol : 72 * mem;
                    const int c1 = ti < 2 ? 256 * grp + 128 * ti : ti < 5 ? 192 * (ti - 2) : ti < 8 ? 192 * (ti - 5) : 288 * grp + 96 * (ti - 8);
                    tma2d(sb + off, tm, c0, c1, bar);
                    ti++;
                }
            }
        }
        return;
    }

    const int g = lane >> 2, t = lane & 3;
    const uint32_t act = sb + OFF_ACT, red = sb + OFF_RED, stat = sb + OFF_STAT;
    const uint32_t act_row = act + warp * ACT_PITCH;

    uint32_t xpair = 0;
    uint32_t cv[9];
    {
        unsigned ep = 0;
        if (tid == 0) asm volatile("ld.relaxed.gpu.global.u32 %0, [%1];" : "=r"(ep) : "l"(&scr->epoch) : "memory");
        if (cta < 36) {
            const int sub = tid & 3, row = tid >> 2;
            const char* src = reinterpret_cast<const char*>(prm.wmod) + row * (6 * DM * 2) + ((sub >> 1) * DM + 16 * cta) * 2 + (sub & 1) * 16;
            const uint32_t dst = sb + P_A + row * 64 + ((sub ^ ((row >> 1) & 3)) << 4);
#pragma unroll
            for (int j = 0; j < 9; j++)
                asm volatile("cp.async.cg.shared.global [%0], [%1], 16;" ::"r"(dst + j * 64 * 64), "l"(src + (size_t)j * 64 * (6 * DM * 2)) : "memory");
        }
        if (cta < 36 || extra) {
            const uint32_t* crow = reinterpret_cast<const uint32_t*>(prm.c + warp * DM) + lane;
#pragma unroll
            for (int k = 0; k < 9; k++) cv[k] = __ldg(crow + 32 * k);
        }
        if (extra) {
#pragma unroll 1
            for (int i = tid; i < 2304; i += 256) ll_st(&scr->mod[i / 288][288 * (cta - NCTA) + i % 288], 0, 0);
        } else if (tid < 128) {
            ll_st(&scr->q[grp][tid >> 4][16 * mem + (tid & 15)], 0, 0);
            if (cta < 36 && tid < 24) ll_st128(&scr->h0[tid / 3][3 * cta + tid % 3][0], 0, 0, 0, 0);
        }
        if (cta < 36) {
            const uint32_t* xrow = reinterpret_cast<const uint32_t*>(prm.x + warp * DM) + lane;
            uint32_t xv[9];
#pragma unroll
            for (int k = 0; k < 9; k++) xv[k] = __ldg(xrow + 32 * k);
            if (tid < 64) xpair = __ldg(reinterpret_cast<const uint32_t*>(prm.x + (tid >> 3) * DM + 16 * cta) + (tid & 7));
            float mean, den;
            ln_stats<false>(xv, mean, den);
            if (lane == 0) sts64f(stat + 8 * warp, mean, den);
        }
        if (tid == 0) sts32(stat + 64, ep + 1);
    }
    asm volatile("bar.sync 2, 288;" ::: "memory");
    const uint32_t tag = lds32(stat + 64);

    const int xcol = 1152 + DM * (cta - NCTA);
    auto issue_slice = [&](int it) {
#pragma unroll 1
        for (int p = 0; p < 3; p++) {
            const uint32_t bar = bars + 8 * (BAR_P + 3 * (it & 1) + p);
            mbar_expect_tx(bar, 12288);
            tma2d(sb + ((it & 1) ? P_B : P_A) + p * 12288, &tmMod, xcol + 32 * it, 192 * p, bar);
        }
    };
    if (extra && tid == 0) { issue_slice(0); issue_slice(1); }
    const int nit = extra ? 18 : cta < 36 ? 2 : 1;
#pragma unroll 1
    for (int it = 0; it < nit; it++) {
        const bool crit = cta < 36 && it == 0, is_q = !extra && !crit;
        const int st = extra ? it & 1 : is_q ? 1 : 0;
        const bool stage = !extra || it == 0;
        uint32_t av[9];
        if (!is_q) {
#pragma unroll
            for (int k = 0; k < 9; k++) av[k] = pack_bf16(silu_f(bf_lo(cv[k])), silu_f(bf_hi(cv[k])));
        }
        if (crit) {
            asm volatile("cp.async.wait_all;" ::: "memory");
        } else {
#pragma unroll 1
            for (int p = 0; p < 3; p++) mbar_wait(bars + 8 * (BAR_P + 3 * st + p), extra ? (it >> 1) & 1 : 0);
        }
        uint32_t hw[4][3];
        if (is_q) {
            const u64* hp = &scr->h0[warp][lane][0];
            const u64* hl = &scr->h0[warp][96 + (lane < 12 ? lane : 0)][0];
            int pit = 0;
            uint32_t bad;
            do {
                bad = 0;
#pragma unroll
                for (int k = 0; k < 4; k++) {
                    uint32_t tg;
                    ll_ld128(k < 3 ? hp + 64 * k : hl, hw[k][0], hw[k][1], hw[k][2], tg);
                    bad |= tg ^ tag;
                }
            } while (!poll_done(bad, pit));
        }
        if (it > 0) cbar();
        if (is_q) {
#pragma unroll
            for (int k = 0; k < 4; k++) {
                const int pk = lane + 32 * k, c = pk / 3, j = pk - 3 * c;
                if (k < 3 || lane < 12) {
                    const uint32_t a = act_row + 4 * (8 * c + 3 * j);
                    sts32(a, hw[k][0]); sts32(a + 4, hw[k][1]);
                    if (j < 2) sts32(a + 8, hw[k][2]);
                }
            }
        } else if (stage) {
#pragma unroll
            for (int k = 0; k < 9; k++) sts32(act_row + 4 * (lane + 32 * k), av[k]);
        }
        if (stage) cbar();
        {
            const int mt = warp & 1, kg = warp >> 1;
            const int rl = (lane & 7) + ((lane >> 4) << 3);
            const uint32_t aaddr = sb + (st ? P_B : P_A) + (144 * kg + rl) * 64 + (((2 * mt + ((lane >> 3) & 1)) ^ ((rl >> 1) & 3)) << 4);
            const uint32_t baddr = act + (lane & 7) * ACT_PITCH + ((lane >> 3) & 1) * 16 + 288 * kg;
            float c0[4] = {0.f, 0.f, 0.f, 0.f}, c1[4] = {0.f, 0.f, 0.f, 0.f};
#pragma unroll
            for (int i = 0; i < 9; i++) {
                uint32_t a[4], b0, b1;
                ldsm4t(a, aaddr + i * 16 * 64);
                ldsm2(b0, b1, baddr + i * 32);
                if (i & 1) mma16816(c1, a, b0, b1); else mma16816(c0, a, b0, b1);
            }
            const uint32_t dst = red + warp * 512 + g * 32 + t * 8;
            sts64f(dst, c0[0] + c1[0], c0[1] + c1[1]);
            sts64f(dst + 256, c0[2] + c1[2], c0[3] + c1[3]);
        }
        cbar();
        if (tid == 0) {
            if (extra) {
                if (it + 2 < nit) issue_slice(it + 2);
            } else if (st == 0) {
                mbar_arrive_n(bars + 8 * (BAR_EMPTY + 3), 4); mbar_arrive_n(bars + 8 * (BAR_EMPTY + 4), 4);
            } else {
                mbar_arrive_n(bars + 8 * (BAR_EMPTY + 5), 4); mbar_arrive_n(bars + 8 * (BAR_EMPTY + 6), 4);
                mbar_arrive_n(bars + 8 * (BAR_EMPTY + 7), 4);
            }
        }
        if (tid < 128) {
            const int b = crit ? (tid >> 3) & 7 : tid >> 4, cp = crit ? tid & 7 : tid & 15;
            const uint32_t ra = red + (cp >> 3) * 512 + (2 * (cp & 7)) * 32 + b * 4;
            const float v0 = (ldsf(ra) + ldsf(ra + 1024)) + (ldsf(ra + 2048) + ldsf(ra + 3072));
            const float v1 = (ldsf(ra + 32) + ldsf(ra + 1056)) + (ldsf(ra + 2080) + ldsf(ra + 3104));
            uint32_t val = pack_bf16(v0, v1);
            if (crit) {
                const uint32_t ca = pack_bf16((ldsf(ra + 512) + ldsf(ra + 1536)) + (ldsf(ra + 2560) + ldsf(ra + 3584)),
                                              (ldsf(ra + 544) + ldsf(ra + 1568)) + (ldsf(ra + 2592) + ldsf(ra + 3616)));
                const float mean = ldsf(stat + 8 * b), den = ldsf(stat + 8 * b + 4);
                const uint32_t d = bf2_sub(xpair, pack_bf16(mean, mean));
                const uint32_t n = pack_bf16(__fdiv_rn(bf_lo(d), den), __fdiv_rn(bf_hi(d), den));
                val = bf2_add(bf2_mul(n, bf2_add(BF2_ONE, ca)), val);
                const uint32_t w1 = __shfl_down_sync(0xffffffffu, val, 1), w2 = __shfl_down_sync(0xffffffffu, val, 2);
                if (tid < 64 && cp % 3 == 0) ll_st128(&scr->h0[b][3 * cta + cp / 3][0], val, w1, cp < 6 ? w2 : 0u, tag);
            } else {
                ll_st(is_q ? &scr->q[grp][b][16 * mem + cp] : &scr->mod[b][288 * (cta - NCTA) + 16 * it + cp], val, tag);
            }
        }
    }
    if (extra) return;
    cbar();
    const uint32_t actb = sb + OFF_ACTB;
    const int rb = grp >> 1;
    const int rpair = 36 * mem + 18 * (grp & 1) + (lane < 18 ? lane : 0);
    uint32_t x_r = 0, ga_r = 0, gb_r = 0;
    uint32_t sbv[9], cbv[9];
#pragma unroll
    for (int k = 0; k < 9; k++) sbv[k] = cbv[k] = 0;

    float oacc[8][4];
#pragma unroll
    for (int m = 0; m < 8; m++) { oacc[m][0] = oacc[m][1] = oacc[m][2] = oacc[m][3] = 0.f; }
    float m0 = -INFINITY, m1 = -INFINITY, l0 = 0.f, l1 = 0.f;
    const float SC = 1.4426950408889634f;
    {
        uint32_t qf[16];
        {
            uint32_t qv[1];
            ll_poll<1, 0>(&scr->q[grp][mem][16 * warp + (lane & 15)], tag, qv);
            if (lane < 16) sts32(actb + 4 * (16 * warp + lane), qv[0]);
            cbar();
#pragma unroll
            for (int k = 0; k < 16; k++) qf[k] = lds32(actb + 4 * ((g & 1) * 64 + t + 4 * k));
        }
        const int gi = warp >> 2, wq = warp & 3;
        const uint32_t offK = (16 * wq + (lane & 7) + (((lane >> 3) & 1) << 3)) * 128;
        const uint32_t offV = (16 * wq + (lane & 7) + ((lane >> 4) << 3)) * 128;
        const uint32_t xK = ((lane >> 4) ^ (lane & 7)) << 4, xV = (((lane >> 3) & 1) ^ (lane & 7)) << 4;
        int slot = (TILE0 + 2 * gi) % NSLOT, use = (TILE0 + 2 * gi) / NSLOT;
#pragma unroll 1
        for (int kb = gi; kb < NTILES / 2; kb += 2) {
            if (kb - gi == MID_KB) {
                if (warp == 7) {
                    x_r = __ldg(reinterpret_cast<const uint32_t*>(prm.x + rb * DM) + rpair);
                    uint32_t gg[2];
                    ll_poll<2, 864>(&scr->mod[rb][rpair], tag, gg);
                    ga_r = gg[0]; gb_r = gg[1];
                }
                {
                    const u64* mp = &scr->mod[warp][288 + 3 * lane];
                    int it = 0;
                    uint32_t bad;
                    do {
                        bad = 0;
#pragma unroll
                        for (int k = 0; k < 9; k++) {
                            uint32_t t0, t1;
                            ll_ld(mp + 96 * (k / 3) + k % 3, sbv[k], t0);
                            ll_ld(mp + 288 + 96 * (k / 3) + k % 3, cbv[k], t1);
                            bad |= (t0 ^ tag) | (t1 ^ tag);
                        }
                    } while (!poll_done(bad, it));
#pragma unroll
                    for (int k = 0; k < 9; k++) cbv[k] = bf2_add(BF2_ONE, cbv[k]);
                }
                if (tid < 128) ll_st(&scr->o[grp][mem][tid], 0, 0);
                if (tid < 144) ll_st(&scr->hh[grp][18 * mem][0] + tid, 0, 0);
                if (tid < 6) ll_st128(&scr->x1[rb][12 * mem + 6 * (grp & 1) + tid][0], 0, 0, 0, 0);
#pragma unroll 1
                for (int i = tid; i < 576; i += 256) {
                    const int kq = i / 36;
                    u64* pp = &scr->p1[mem][kq][grp][i - 36 * kq];
                    ll_st(pp, 0, 0); ll_st(pp + P2_MINUS_P1, 0, 0);
                }
            }
            const uint32_t kt = sb + slot * SLOT + offK;
            mbar_wait(bars + 8 * (BAR_FULL + slot), use & 1);
            float sa[4] = {0.f, 0.f, 0.f, 0.f}, sc2[4] = {0.f, 0.f, 0.f, 0.f};
#pragma unroll
            for (int ks = 0; ks < 8; ks++) {
                uint32_t a[4];
                ldsm4(a, kt + (ks >> 2) * 8192 + (xK ^ ((ks & 3) << 5)));
                if (ks & 1) mma16816(sc2, a, qf[2 * ks], qf[2 * ks + 1]); else mma16816(sa, a, qf[2 * ks], qf[2 * ks + 1]);
            }
            __syncwarp();
            if (lane == 0) mbar_arrive(bars + 8 * (BAR_EMPTY + slot));
            const uint32_t r01 = pack_bf16(sa[0] + sc2[0], sa[1] + sc2[1]), r23 = pack_bf16(sa[2] + sc2[2], sa[3] + sc2[3]);
            const float RS = 0.08838834764831845f;
            const uint32_t u01 = pack_bf16(bf_lo(r01) * RS, bf_hi(r01) * RS), u23 = pack_bf16(bf_lo(r23) * RS, bf_hi(r23) * RS);
            const float s0 = bf_lo(u01), s1 = bf_hi(u01), s2 = bf_lo(u23), s3 = bf_hi(u23);
            const bool grow = (s0 > m0) || (s2 > m0) || (s1 > m1) || (s3 > m1);
            if (__any_sync(0xffffffffu, grow)) {
                float n0 = fmaxf(s0, s2), n1 = fmaxf(s1, s3);
#pragma unroll
                for (int o = 4; o < 32; o <<= 1) {
                    n0 = fmaxf(n0, __shfl_xor_sync(0xffffffffu, n0, o));
                    n1 = fmaxf(n1, __shfl_xor_sync(0xffffffffu, n1, o));
                }
                n0 = fmaxf(n0, m0); n1 = fmaxf(n1, m1);
                const float a0 = ex2((m0 - n0) * SC), a1 = ex2((m1 - n1) * SC);
                m0 = n0; m1 = n1; l0 *= a0; l1 *= a1;
#pragma unroll
                for (int m = 0; m < 8; m++) { oacc[m][0] *= a0; oacc[m][1] *= a1; oacc[m][2] *= a0; oacc[m][3] *= a1; }
            }
            const float mc0 = m0 * SC, mc1 = m1 * SC;
            const float p0 = ex2(fmaf(s0, SC, -mc0)), p1 = ex2(fmaf(s1, SC, -mc1));
            const float p2 = ex2(fmaf(s2, SC, -mc0)), p3 = ex2(fmaf(s3, SC, -mc1));
            l0 += p0 + p2; l1 += p1 + p3;
            const uint32_t pb0 = movmat(pack_bf16(p0, p1)), pb1 = movmat(pack_bf16(p2, p3));
            const uint32_t vt = sb + (slot + 1) * SLOT + offV;
            mbar_wait(bars + 8 * (BAR_FULL + slot + 1), use & 1);
#pragma unroll
            for (int mt = 0; mt < 8; mt++) {
                uint32_t a[4];
                ldsm4t(a, vt + (mt >> 2) * 8192 + (xV ^ ((mt & 3) << 5)));
                mma16816(oacc[mt], a, pb0, pb1);
            }
            __syncwarp();
            if (lane == 0) mbar_arrive(bars + 8 * (BAR_EMPTY + slot + 1));
            slot += 4;
            if (slot >= NSLOT) { slot -= NSLOT; use++; }
        }
    }

    {
#pragma unroll
        for (int o = 4; o < 32; o <<= 1) { l0 += __shfl_xor_sync(0xffffffffu, l0, o); l1 += __shfl_xor_sync(0xffffffffu, l1, o); }
        const uint32_t ro = red + warp * 1024 + g * 8;
#pragma unroll
        for (int mt = 0; mt < 8; mt++) {
            if (t == (mt >> 1)) {
                sts64f(ro + mt * 128, oacc[mt][0], oacc[mt][1]);
                sts64f(ro + mt * 128 + 64, oacc[mt][2], oacc[mt][3]);
            }
        }
        if (lane == 0) sts128f(red + 8192 + warp * 16, m0, m1, l0, l1);
        u64* po = &scr->o[grp][mem][tid & 127];
        uint32_t rv = red + (tid & 63) * 16;
        PIN64(po); PIN32(rv);
        cbar();
        if (tid < 128) {
            const bool h = tid >= 64;
            float mw[8], lw[8], v0[8], v1[8];
#pragma unroll
            for (int w = 0; w < 8; w++) {
                const float4 a = lds128f(red + 8192 + w * 16), v = lds128f(rv + w * 1024);
                mw[w] = h ? a.y : a.x; lw[w] = h ? a.w : a.z;
                v0[w] = h ? v.y : v.x; v1[w] = h ? v.w : v.z;
            }
            const float M = fmaxf(fmaxf(fmaxf(mw[0], mw[1]), fmaxf(mw[2], mw[3])), fmaxf(fmaxf(mw[4], mw[5]), fmaxf(mw[6], mw[7])));
            float L = 0.f, o0 = 0.f, o1 = 0.f;
#pragma unroll
            for (int w = 0; w < 8; w++) {
                const float f = ex2((mw[w] - M) * SC);
                L = fmaf(f, lw[w], L); o0 = fmaf(f, v0[w], o0); o1 = fmaf(f, v1[w], o1);
            }
            const float inv = __fdividef(1.f, L);
            ll_st(po, pack_bf16(o0 * inv, o1 * inv), tag);
        }
    }
    const int rl = (lane & 7) + ((lane >> 4) << 3);
    const uint32_t a72 = sb + rl * 144 + (2 * warp + ((lane >> 3) & 1)) * 16;
    u64 *pw0, *pw1;
    {
        const int c0 = min(16 * warp + g, 71), c1 = min(16 * warp + g + 8, 71);
        u64* pb = &scr->p1[mem][4 * t][grp][0];
        pw0 = pb + (c0 >= 36 ? 576 + c0 - 36 : c0);
        pw1 = pb + (c1 >= 36 ? 576 + c1 - 36 : c1);
    }
    const bool hi_ok = warp < 4;
    {
        uint32_t wa[16][4];
        mbar_wait(bars + 8 * (BAR_T + 0), 0);
        mbar_wait(bars + 8 * (BAR_T + 1), 0);
        gemv72_load<16>(wa, a72 + T_WO);
        const u64* po = &scr->o[grp][warp][lane];
        uint32_t dst = actb + warp * ACTB_O_PITCH + lane * 4;
        uint32_t baddr = actb + (lane & 7) * ACTB_O_PITCH + (lane >> 3) * 16;
        PIN64(pw0); PIN64(pw1); PIN32(dst); PIN32(baddr);
        uint32_t ov[4];
        ll_poll<4, 32>(po, tag, ov);
#pragma unroll
        for (int k = 0; k < 4; k++) sts32(dst + 128 * k, ov[k]);
        cbar();
        if (warp < 5) gemv72_run<16>(wa, baddr, pw0, pw1, hi_ok, tag);
    }
    uint32_t x1_r = 0;
    const u64* pr = &scr->p1[mem][grp][2 * warp][lane < 18 ? 2 * lane : 0];
    {
        u64* px = &scr->x1[rb][12 * mem + 6 * (grp & 1) + (lane < 6 ? lane : 0)][0];
        int src = lane < 6 ? 3 * lane : 0;
        PIN64(px); PIN32(src);
        float a0 = 0.f, a1 = 0.f;
        reduce16(pr, red, warp, lane, tag, a0, a1);
        if (warp == 7) {
            x1_r = pack_bf16(fmaf(bf_lo(ga_r), a0, bf_lo(x_r)), fmaf(bf_hi(ga_r), a1, bf_hi(x_r)));
            const uint32_t w0 = __shfl_sync(0xffffffffu, x1_r, src), w1 = __shfl_sync(0xffffffffu, x1_r, src + 1),
                           w2 = __shfl_sync(0xffffffffu, x1_r, src + 2);
            if (lane < 6) ll_st128(px, w0, w1, w2, tag);
        }
    }
    {
        const int mat = warp >> 2, kg = warp & 3;
#pragma unroll 1
        for (int p = 0; p < 3; p++) mbar_wait(bars + 8 * (BAR_T + 2 + 3 * mat + p), 0);
        const uint32_t aaddr = sb + (mat ? T_WU : T_WG) + (144 * kg + rl) * 80 + ((lane >> 3) & 1) * 16;
        uint32_t wa[9][3][4];
#pragma unroll
        for (int i = 0; i < 6; i++)
#pragma unroll
            for (int m = 0; m < 3; m++) ldsm4t(wa[i][m], aaddr + i * 16 * 80 + m * 32);

        const u64* xp = &scr->x1[warp][lane][0];
        uint32_t adst = act_row + 12 * lane;
        uint32_t baddr = act + (lane & 7) * ACT_PITCH + (lane >> 3) * 16 + 288 * kg;
        PIN32(adst); PIN32(baddr);
        asm volatile("bar.sync 4, 256;" ::: "memory");
        uint32_t xv[9];
        {
            int it = 0;
            uint32_t bad;
            do {
                bad = 0;
#pragma unroll
                for (int k = 0; k < 3; k++) {
                    uint32_t tg;
                    ll_ld128(xp + 64 * k, xv[3 * k], xv[3 * k + 1], xv[3 * k + 2], tg);
                    bad |= tg ^ tag;
                }
            } while (!poll_done(bad, it));
        }
        float mean, den;
        ln_stats<true>(xv, mean, den);
        const uint32_t m2 = pack_bf16(mean, mean);
        float rinv;
        asm("rcp.approx.f32 %0, %1;" : "=f"(rinv) : "f"(den));
#pragma unroll
        for (int k = 0; k < 9; k++) sts32(adst + 384 * (k / 3) + 4 * (k % 3), ln_mod2(xv[k], m2, rinv, cbv[k], sbv[k]));
#pragma unroll
        for (int i = 6; i < 9; i++)
#pragma unroll
            for (int m = 0; m < 3; m++) ldsm4t(wa[i][m], aaddr + i * 16 * 80 + m * 32);
        uint32_t rdst = red + warp * 1536 + g * 32 + t * 8;
        uint32_t rsrc = red + (((36 * cta) & 7) + 2 * (tid >> 3)) * 32 + (tid & 7) * 4;
        u64* ph = &scr->hh[grp][18 * mem][0] + (tid < 144 ? tid : 0);
        PIN32(rdst); PIN32(rsrc); PIN64(ph);
        cbar();
        float c[2][3][4];
#pragma unroll
        for (int m = 0; m < 3; m++)
#pragma unroll
            for (int j = 0; j < 4; j++) c[0][m][j] = c[1][m][j] = 0.f;
#pragma unroll
        for (int i = 0; i < 9; i += 2) {
            uint32_t b[4];
            ldsm4(b, baddr + i * 32);
#pragma unroll
            for (int m = 0; m < 3; m++) {
                mma16816(c[0][m], wa[i][m], b[0], b[1]);
                if (i + 1 < 9) mma16816(c[1][m], wa[i + 1][m], b[2], b[3]);
            }
        }
#pragma unroll
        for (int m = 0; m < 3; m++) {
            sts64f(rdst + m * 512, c[0][m][0] + c[1][m][0], c[0][m][1] + c[1][m][1]);
            sts64f(rdst + m * 512 + 256, c[0][m][2] + c[1][m][2], c[0][m][3] + c[1][m][3]);
        }
        cbar();
        if (tid < 144) {
            float r[2];
#pragma unroll
            for (int e = 0; e < 2; e++) {
                const uint32_t a = rsrc + 32 * e;
                const float gg = (ldsf(a) + ldsf(a + 1536)) + (ldsf(a + 3072) + ldsf(a + 4608));
                const float uu = (ldsf(a + 6144) + ldsf(a + 7680)) + (ldsf(a + 9216) + ldsf(a + 10752));
                r[e] = gelu_f(gg) * uu;
            }
            ll_st(ph, pack_bf16(r[0], r[1]), tag);
        }
        if (cta == 0 && tid == 255) {
            asm volatile("st.relaxed.gpu.global.u32 [%0], %1;" ::"l"(&scr->epoch), "r"(tag) : "memory");
            asm volatile("st.relaxed.gpu.global.u32 [%0], %1;" ::"l"(&scr->prog), "r"(0u) : "memory");
        }
    }
    {
        uint32_t wa[18][4];
#pragma unroll 1
        for (int p = 0; p < 3; p++) mbar_wait(bars + 8 * (BAR_T + 8 + p), 0);
        gemv72_load<18>(wa, a72 + T_WD);
        const u64* hp = &scr->hh[grp][0][0] + tid;
        const u64* hl = &scr->hh[grp][128][0] + (tid & 127);
        uint32_t dst = actb + (tid & 7) * ACTB_H_PITCH + (tid >> 3) * 4;
        uint32_t dl = actb + (tid & 7) * ACTB_H_PITCH + (128 + ((tid & 127) >> 3)) * 4;
        uint32_t baddr = actb + (lane & 7) * ACTB_H_PITCH + (lane >> 3) * 16;
        u64 *q0 = pw0 + P2_MINUS_P1, *q1 = pw1 + P2_MINUS_P1;
        PIN32(dst); PIN32(dl); PIN32(baddr); PIN64(q0); PIN64(q1);
        uint32_t hv[5];
        {
            int it = 0;
            uint32_t bad;
            do {
                bad = 0;
#pragma unroll
                for (int k = 0; k < 5; k++) { uint32_t tg; ll_ld(k < 4 ? hp + 256 * k : hl, hv[k], tg); bad |= tg ^ tag; }
            } while (!poll_done(bad, it));
        }
#pragma unroll
        for (int k = 0; k < 4; k++) sts32(dst + 128 * k, hv[k]);
        sts32(dl, hv[4]);
        cbar();
        if (warp < 5) gemv72_run<18>(wa, baddr, q0, q1, hi_ok, tag);
    }
    {
        uint32_t* po = reinterpret_cast<uint32_t*>(prm.out + rb * DM) + rpair;
        PIN64(po);
        float a0 = 0.f, a1 = 0.f;
        reduce16(pr + P2_MINUS_P1, red, warp, lane, tag, a0, a1);
        if (warp == 7) {
            if (lane < 18) *po = pack_bf16(fmaf(bf_lo(gb_r), a0, bf_lo(x1_r)), fmaf(bf_hi(gb_r), a1, bf_hi(x1_r)));
        }
    }
}

typedef CUresult (*EncodeFn)(CUtensorMap*, CUtensorMapDataType, cuuint32_t, void*, const cuuint64_t*, const cuuint64_t*,
                             const cuuint32_t*, const cuuint32_t*, CUtensorMapInterleave, CUtensorMapSwizzle,
                             CUtensorMapL2promotion, CUtensorMapFloatOOBfill);

void make_map2d(EncodeFn enc, CUtensorMap* m, const void* ptr, uint64_t cols, uint64_t rows, uint32_t bc, uint32_t br,
                CUtensorMapSwizzle sw, CUtensorMapL2promotion pr) {
    cuuint64_t dims[2] = {cols, rows};
    cuuint64_t strides[1] = {cols * 2};
    cuuint32_t box[2] = {bc, br};
    cuuint32_t es[2] = {1, 1};
    enc(m, CU_TENSOR_MAP_DATA_TYPE_BFLOAT16, 2, const_cast<void*>(ptr), dims, strides, box, es,
        CU_TENSOR_MAP_INTERLEAVE_NONE, sw, pr, CU_TENSOR_MAP_FLOAT_OOB_FILL_NONE);
}
void make_map_kv(EncodeFn enc, CUtensorMap* m, const void* ptr) {
    cuuint64_t dims[3] = {64, (cuuint64_t)NB * 16 * SK, 2};
    cuuint64_t strides[2] = {256, 128};
    cuuint32_t box[3] = {64, 64, 2};
    cuuint32_t es[3] = {1, 1, 1};
    enc(m, CU_TENSOR_MAP_DATA_TYPE_BFLOAT16, 3, const_cast<void*>(ptr), dims, strides, box, es,
        CU_TENSOR_MAP_INTERLEAVE_NONE, CU_TENSOR_MAP_SWIZZLE_128B, CU_TENSOR_MAP_L2_PROMOTION_L2_256B,
        CU_TENSOR_MAP_FLOAT_OOB_FILL_NONE);
}

}

extern "C" void kernel_launch(void* const* d_in, const int* in_sizes, int n_in, void* d_out, int out_size) {
    (void)in_sizes; (void)n_in; (void)out_size;
    static EncodeFn enc = nullptr;
    static Scratch* scr = nullptr;
    if (!enc) {
        void* fn = nullptr;
        cudaDriverEntryPointQueryResult qr;
        cudaGetDriverEntryPoint("cuTensorMapEncodeTiled", &fn, cudaEnableDefault, &qr);
        enc = (EncodeFn)fn;
        cudaGetSymbolAddress((void**)&scr, g_scr);
        cudaFuncSetAttribute(adaln_gqa_geglu_decode_kernel, cudaFuncAttributeMaxDynamicSharedMemorySize, SMEM_BYTES);
    }
    CUtensorMap tmK, tmV, tmMod, tmWq, tmWo, tmWg, tmWu, tmWd;
    make_map_kv(enc, &tmK, d_in[1]);
    make_map_kv(enc, &tmV, d_in[2]);
    make_map2d(enc, &tmMod, d_in[10], 6 * DM, DM, 32, 192, CU_TENSOR_MAP_SWIZZLE_64B, CU_TENSOR_MAP_L2_PROMOTION_L2_128B);
    make_map2d(enc, &tmWq, d_in[3], 4096, DM, 32, 192, CU_TENSOR_MAP_SWIZZLE_64B, CU_TENSOR_MAP_L2_PROMOTION_L2_128B);
    make_map2d(enc, &tmWo, d_in[4], DM, 4096, 72, 128, CU_TENSOR_MAP_SWIZZLE_NONE, CU_TENSOR_MAP_L2_PROMOTION_L2_128B);
    make_map2d(enc, &tmWg, d_in[6], DF, DM, 40, 192, CU_TENSOR_MAP_SWIZZLE_NONE, CU_TENSOR_MAP_L2_PROMOTION_L2_128B);
    make_map2d(enc, &tmWu, d_in[7], DF, DM, 40, 192, CU_TENSOR_MAP_SWIZZLE_NONE, CU_TENSOR_MAP_L2_PROMOTION_L2_128B);
    make_map2d(enc, &tmWd, d_in[8], DM, DF, 72, 96, CU_TENSOR_MAP_SWIZZLE_NONE, CU_TENSOR_MAP_L2_PROMOTION_L2_128B);
    Params prm;
    prm.x = (const __nv_bfloat16*)d_in[0];
    prm.c = (const __nv_bfloat16*)d_in[9];
    prm.wmod = (const __nv_bfloat16*)d_in[10];
    prm.out = (__nv_bfloat16*)d_out;
    prm.scr = scr;
    adaln_gqa_geglu_decode_kernel<<<NCTA + NXTRA, NTHREADS, SMEM_BYTES, cudaStreamPerThread>>>(prm, tmK, tmV, tmMod, tmWq, tmWo, tmWg, tmWu, tmWd);
}
```
